```python
import torch

def _softmax(x, axis=-1):
    return torch.softmax(x, dim=axis)

def _gelu(x):
    return torch.nn.functional.gelu(x, approximate='tanh')

def _silu(x):
    return torch.nn.functional.silu(x)

def _sigmoid(x):
    return torch.sigmoid(x)

def _layernorm(x, axis=-1, eps=1e-05):
    m = x.mean(dim=axis, keepdim=True)
    v = x.var(dim=axis, keepdim=True, unbiased=False)
    return (x - m) / torch.sqrt(v + eps)

def _scatter_add(tgt, idx, src, axis=0):
    return tgt.clone().index_add_(axis, idx, src)

def _segment_sum(src, seg, n):
    out = torch.zeros((n,) + src.shape[1:], dtype=src.dtype)
    return out.index_add_(0, seg, src)

def _pad(x, pw):
    flat = tuple((v for pair in reversed(pw) for v in pair))
    return torch.nn.functional.pad(x, flat)
kernel_name = 'adaLN_cond__sliding_block_cached__glu_gated_swiglu__decode'

def setup_inputs():

    _w = lambda a: (lambda t: t.to(torch.bfloat16) if t.is_floating_point() else t)(torch.as_tensor(a))

    def _A_setup():
        B, Sq, D = (2, 1, 1024)
        Hq, Hkv, Sk, Dh = (32, 4, 32768, 128)
        assert Hq % Hkv == 0, (Hq, Hkv)
        return {'x': _w((lambda *s: torch.randn(*s, dtype=torch.bfloat16) * 0.05)(B, Sq, D)), 'k_cache': _w((lambda *s: torch.randn(*s, dtype=torch.bfloat16) * 3.2)(B, Hkv, Sk, Dh)), 'v_cache': _w((lambda *s: torch.randn(*s, dtype=torch.bfloat16) * 3.2)(B, Hkv, Sk, Dh)), 'wq': _w((lambda *s: torch.randn(*s, dtype=torch.bfloat16) * 3.2)(D, Hq * Dh) * D ** (-0.5)), 'wo': _w((lambda *s: torch.randn(*s, dtype=torch.bfloat16) * 3.2)(Hq * Dh, D) * (Hq * Dh) ** (-0.5))}
    _A_in = _A_setup()

    def _B_setup():
        B, S, D, F = (2, 1, 1024, 3584)
        return {'x': _w((lambda *s: torch.randn(*s, dtype=torch.bfloat16) * 0.05)(B, S, D)), 'w1': _w((lambda *s: torch.randn(*s, dtype=torch.bfloat16) * 1.6)(D, F) * (2.0 / D) ** 0.5), 'w3': _w((lambda *s: torch.randn(*s, dtype=torch.bfloat16) * 1.6)(D, F) * (2.0 / D) ** 0.5), 'w2': _w((lambda *s: torch.randn(*s, dtype=torch.bfloat16) * 1.6)(F, D) * (2.0 / F) ** 0.5)}
    _B_in = _B_setup()
    return {'A_x': _A_in['x'], 'A_k_cache': _A_in['k_cache'], 'A_v_cache': _A_in['v_cache'], 'A_wq': _A_in['wq'], 'A_wo': _A_in['wo'], 'B_x': _B_in['x'], 'B_w1': _B_in['w1'], 'B_w3': _B_in['w3'], 'B_w2': _B_in['w2'], 'c': _w((lambda *s: torch.randn(*s, dtype=torch.bfloat16) * 0.2)(2, 1024) * 8.0), 'w_mod': _w((lambda *s: torch.randn(*s, dtype=torch.bfloat16) * 0.2)(1024, 6 * 1024) * 1024 ** (-0.5) * 8.0)}

def reference(A_x, A_k_cache, A_v_cache, A_wq, A_wo, B_x, B_w1, B_w3, B_w2, c, w_mod):

    def _A_ref(x, k_cache, v_cache, wq, wo):
        B, Sq, D = x.shape
        Hq, Dh = (32, 128)
        Hkv, Sk = (k_cache.shape[1], k_cache.shape[2])
        W = min(4096, max(256, Sk // 4))
        rep = Hq // Hkv
        q = (lambda x, *d: x.permute(*d))((x @ wq).reshape(B, Sq, Hq, Dh), 0, 2, 1, 3)
        k = (lambda x, n, axis: torch.repeat_interleave(x, n, dim=axis))(k_cache[:, :, Sk - W:, :], rep, axis=1)
        v = (lambda x, n, axis: torch.repeat_interleave(x, n, dim=axis))(v_cache[:, :, Sk - W:, :], rep, axis=1)
        scores = torch.einsum('bhqd,bhkd->bhqk', q, k) * Dh ** (-0.5)
        p = _softmax(scores, axis=-1)
        o = torch.einsum('bhqk,bhkd->bhqd', p, v)
        return (lambda x, *d: x.permute(*d))(o, 0, 2, 1, 3).reshape(B, Sq, Hq * Dh) @ wo

    def _B_ref(x, w1, w3, w2):
        gate = torch.einsum('bsd,df->bsf', x, w1)
        up = torch.einsum('bsd,df->bsf', x, w3)
        h = _silu(gate) * up
        out = torch.einsum('bsf,fd->bsd', h, w2)
        return out
    x = A_x
    mod = (_silu(c) @ w_mod).reshape(c.shape[0], 6, 1, -1)
    sa, ca, ga, sb, cb, gb = (mod[:, 0].clone(), mod[:, 1].clone(), mod[:, 2].clone(), mod[:, 3].clone(), mod[:, 4].clone(), mod[:, 5].clone())
    h = _layernorm(x, axis=-1) * (1 + ca) + sa
    x = x + ga * _A_ref(h, A_k_cache, A_v_cache, A_wq, A_wo)
    h = _layernorm(x, axis=-1) * (1 + cb) + sb
    x = x + gb * _B_ref(h, B_w1, B_w3, B_w2)
    return x
```

```cpp
#include <cuda_runtime.h>
#include <cuda_bf16.h>
#include <cuda.h>
#include <stdint.h>

namespace {

constexpr int SK = 32768, WIN = 4096;
constexpr int NCTA = 128;
constexpr int SLOT_BYTES = 16384;
constexpr int BOX_BYTES = 8192;
constexpr int NSLOT = 12;
constexpr int NCHUNK = 33;
#define INFLIGHT 5
constexpr int NTHREADS = 192;

constexpr int OFF_P1 = 0;
constexpr int OFF_P1B = OFF_P1 + 4 * 2048 * 2;
constexpr int OFF_P2 = OFF_P1B + 8 * 3072 * 2;
constexpr int OFF_P3 = OFF_P2 + 4 * 2 * 4096;
constexpr int OFF_ML = OFF_P3 + 2 * 32 * 16 * 128;
constexpr int OFF_P4 = OFF_ML + 2 * 32 * 16 * 2;
constexpr int OFF_X1 = OFF_P4 + 32 * 1024 * 2;
constexpr int OFF_CS = OFF_X1 + 1024 * 2;
constexpr int OFF_GU = OFF_CS + 1024 * 4;
constexpr int OFF_P6 = OFF_GU + 8192 * 2;
constexpr int SCR_FLOATS = OFF_P6 + 8 * 1024 * 2;

__device__ __align__(1024) float g_scr[SCR_FLOATS];
__device__ unsigned g_epoch[NCTA * 8];

constexpr int SM_SILU = NSLOT * SLOT_BYTES;
constexpr int SM_H = SM_SILU + 4096;
constexpr int SM_O = SM_H + 1024;
constexpr int SM_H2 = SM_O + 512;
constexpr int SM_HH = SM_H2 + 4096;
constexpr int SM_Q = SM_HH + 2048;
constexpr int SM_P = SM_Q + 2048;
constexpr int SM_RED = SM_P + 4096;
constexpr int SM_BAR = SM_RED + 512;
constexpr int SM_TOTAL = SM_BAR + 256;

struct Params {
    CUtensorMap tm[8];
    const __nv_bfloat16* x;
    const __nv_bfloat16* c;
    __nv_bfloat16* out;
};

constexpr int SPIN_LIMIT = 1 << 22;

__device__ __forceinline__ uint32_t smem_u32(const void* p) { return (uint32_t)__cvta_generic_to_shared(p); }
__device__ __forceinline__ void mbar_init(uint32_t bar, int cnt) {
    asm volatile("mbarrier.init.shared::cta.b64 [%0], %1;" ::"r"(bar), "r"(cnt) : "memory");
}
__device__ __forceinline__ void mbar_expect(uint32_t bar, uint32_t bytes) {
    asm volatile("mbarrier.arrive.expect_tx.shared::cta.b64 _, [%0], %1;" ::"r"(bar), "r"(bytes) : "memory");
}
__device__ __forceinline__ void mbar_arrive(uint32_t bar) {
    asm volatile("mbarrier.arrive.shared::cta.b64 _, [%0];" ::"r"(bar) : "memory");
}
__device__ __forceinline__ bool mbar_try(uint32_t bar, uint32_t parity) {
    uint32_t ok;
    asm volatile(
        "{\n.reg .pred p;\nmbarrier.try_wait.parity.shared::cta.b64 p, [%1], %2;\nselp.u32 %0, 1, 0, p;\n}"
        : "=r"(ok)
        : "r"(bar), "r"(parity)
        : "memory");
    return ok != 0;
}
__device__ __forceinline__ void mbar_wait(uint32_t bar, uint32_t parity) {
    int n = 0;
    while (!mbar_try(bar, parity)) {
        if (++n > SPIN_LIMIT) __trap();
    }
}
__device__ __forceinline__ void tma2d(uint32_t dst, const CUtensorMap* tm, int c0, int c1, uint32_t bar, uint64_t pol) {
    asm volatile(
        "cp.async.bulk.tensor.2d.shared::cluster.global.mbarrier::complete_tx::bytes.L2::cache_hint [%0], [%1, {%3, "
        "%4}], [%2], %5;" ::"r"(dst),
        "l"(tm), "r"(bar), "r"(c0), "r"(c1), "l"(pol)
        : "memory");
}
__device__ __forceinline__ void bar_sync(int id, int n) { asm volatile("bar.sync %0, %1;" ::"r"(id), "r"(n) : "memory"); }
__device__ __forceinline__ void bar_arrive(int id, int n) { asm volatile("bar.arrive %0, %1;" ::"r"(id), "r"(n) : "memory"); }

__device__ __forceinline__ uint4 ldp4(const float* p) {
    uint4 v;
    asm volatile("ld.relaxed.gpu.global.v4.u32 {%0,%1,%2,%3}, [%4];"
                 : "=r"(v.x), "=r"(v.y), "=r"(v.z), "=r"(v.w)
                 : "l"(p)
                 : "memory");
    return v;
}
__device__ __forceinline__ uint2 ldp2(const float* p) {
    uint2 v;
    asm volatile("ld.relaxed.gpu.global.v2.u32 {%0,%1}, [%2];" : "=r"(v.x), "=r"(v.y) : "l"(p) : "memory");
    return v;
}
__device__ __forceinline__ void stp1(float* p, uint32_t v) {
    asm volatile("st.relaxed.gpu.global.u32 [%0], %1;" ::"l"(p), "r"(v) : "memory");
}
__device__ __forceinline__ void stp2(float* p, uint32_t a, uint32_t b) {
    asm volatile("st.relaxed.gpu.global.v2.u32 [%0], {%1,%2};" ::"l"(p), "r"(a), "r"(b) : "memory");
}
__device__ __forceinline__ void stp4(float* p, uint32_t a, uint32_t b, uint32_t c, uint32_t d) {
    asm volatile("st.relaxed.gpu.global.v4.u32 [%0], {%1,%2,%3,%4};" ::"l"(p), "r"(a), "r"(b), "r"(c), "r"(d) : "memory");
}
__device__ __forceinline__ uint32_t tagf(float v, uint32_t tag) { return (__float_as_uint(v) & ~1u) | tag; }
__device__ __forceinline__ float untag(uint32_t v) { return __uint_as_float(v & ~1u); }
__device__ __forceinline__ uint32_t bad4(const uint4& v, uint32_t tag) {
    return ((v.x ^ tag) | (v.y ^ tag) | (v.z ^ tag) | (v.w ^ tag)) & 1u;
}
__device__ __forceinline__ uint32_t bad2(const uint2& v, uint32_t tag) { return ((v.x ^ tag) | (v.y ^ tag)) & 1u; }
__device__ __forceinline__ void backoff(int& n) {
    if (++n > SPIN_LIMIT) __trap();
    __nanosleep(40);
}

__device__ __forceinline__ float bf16r(float x) { return __bfloat162float(__float2bfloat16_rn(x)); }
__device__ __forceinline__ uint32_t pack2(float lo, float hi) {
    __nv_bfloat162 v = __floats2bfloat162_rn(lo, hi);
    return *reinterpret_cast<uint32_t*>(&v);
}
__device__ __forceinline__ float bflo(uint32_t w) { return __uint_as_float(w << 16); }
__device__ __forceinline__ float bfhi(uint32_t w) { return __uint_as_float(w & 0xffff0000u); }
__device__ __forceinline__ float silu_f(float x) { return x / (1.0f + __expf(-x)); }

__device__ __forceinline__ void ldsm4t(uint32_t (&a)[4], uint32_t addr) {
    asm volatile("ldmatrix.sync.aligned.m8n8.x4.trans.shared.b16 {%0,%1,%2,%3}, [%4];"
                 : "=r"(a[0]), "=r"(a[1]), "=r"(a[2]), "=r"(a[3])
                 : "r"(addr)
                 : "memory");
}
__device__ __forceinline__ void ldsm4(uint32_t (&a)[4], uint32_t addr) {
    asm volatile("ldmatrix.sync.aligned.m8n8.x4.shared.b16 {%0,%1,%2,%3}, [%4];"
                 : "=r"(a[0]), "=r"(a[1]), "=r"(a[2]), "=r"(a[3])
                 : "r"(addr)
                 : "memory");
}
__device__ __forceinline__ void mma16816(float (&d)[4], const uint32_t (&a)[4], uint32_t b0, uint32_t b1) {
    asm volatile(
        "mma.sync.aligned.m16n8k16.row.col.f32.bf16.bf16.f32 {%0,%1,%2,%3}, {%4,%5,%6,%7}, {%8,%9}, {%0,%1,%2,%3};"
        : "+f"(d[0]), "+f"(d[1]), "+f"(d[2]), "+f"(d[3])
        : "r"(a[0]), "r"(a[1]), "r"(a[2]), "r"(a[3]), "r"(b0), "r"(b1));
}
__device__ __forceinline__ uint4 lds128(uint32_t addr) {
    uint4 v;
    asm volatile("ld.shared.v4.u32 {%0,%1,%2,%3}, [%4];" : "=r"(v.x), "=r"(v.y), "=r"(v.z), "=r"(v.w) : "r"(addr) : "memory");
    return v;
}
__device__ __forceinline__ void sts32(uint32_t addr, uint32_t v) {
    asm volatile("st.shared.u32 [%0], %1;" ::"r"(addr), "r"(v) : "memory");
}
__device__ __forceinline__ void sts16(uint32_t addr, uint16_t v) {
    asm volatile("st.shared.u16 [%0], %1;" ::"r"(addr), "h"(v) : "memory");
}
__device__ __forceinline__ void sts128(uint32_t addr, uint32_t a, uint32_t b, uint32_t c, uint32_t d) {
    asm volatile("st.shared.v4.u32 [%0], {%1,%2,%3,%4};" ::"r"(addr), "r"(a), "r"(b), "r"(c), "r"(d) : "memory");
}
__device__ __forceinline__ void stsf(uint32_t addr, float v) {
    asm volatile("st.shared.f32 [%0], %1;" ::"r"(addr), "f"(v) : "memory");
}
__device__ __forceinline__ float ldsf(uint32_t addr) {
    float v;
    asm volatile("ld.shared.f32 %0, [%1];" : "=f"(v) : "r"(addr) : "memory");
    return v;
}
__device__ __forceinline__ float warp_sum(float v) {
#pragma unroll
    for (int o = 16; o > 0; o >>= 1) v += __shfl_xor_sync(0xffffffffu, v, o);
    return v;
}

#define TSTAMP(i)
#define TSTAMP_W(i, w)

__device__ __forceinline__ void block_sum2(float& a, float& b, uint32_t red, int cw, int lane) {
    a = warp_sum(a);
    b = warp_sum(b);
    if (lane == 0) {
        stsf(red + cw * 8, a);
        stsf(red + cw * 8 + 4, b);
    }
    bar_sync(2, 128);
    a = (ldsf(red) + ldsf(red + 8)) + (ldsf(red + 16) + ldsf(red + 24));
    b = (ldsf(red + 4) + ldsf(red + 12)) + (ldsf(red + 20) + ldsf(red + 28));
}

__device__ __forceinline__ void ln_stats(const float (&v0)[8], const float (&v1)[8], uint32_t red, int cw, int lane,
                                         float& m0, float& m1, float& d0, float& d1) {
    float s0 = 0.f, s1 = 0.f;
#pragma unroll
    for (int j = 0; j < 8; j++) {
        s0 += v0[j];
        s1 += v1[j];
    }
    block_sum2(s0, s1, red, cw, lane);
    const float mean0 = s0 * (1.0f / 1024.0f), mean1 = s1 * (1.0f / 1024.0f);
    float q0 = 0.f, q1 = 0.f;
#pragma unroll
    for (int j = 0; j < 8; j++) {
        float a = v0[j] - mean0, b = v1[j] - mean1;
        q0 += a * a;
        q1 += b * b;
    }
    block_sum2(q0, q1, red + 32, cw, lane);
    m0 = bf16r(mean0);
    m1 = bf16r(mean1);
    d0 = bf16r(sqrtf(bf16r(bf16r(q0 * (1.0f / 1024.0f)) + 1e-5f)));
    d1 = bf16r(sqrtf(bf16r(bf16r(q1 * (1.0f / 1024.0f)) + 1e-5f)));
}
__device__ __forceinline__ float modulate(float x, float m, float d, float c1, float s) {
    float xn = bf16r(__fdiv_rn(bf16r(x - m), d));
    return bf16r(bf16r(xn * c1) + s);
}

__global__ void __launch_bounds__(NTHREADS, 1) fused_kernel(const __grid_constant__ Params prm) {
    extern __shared__ __align__(1024) unsigned char smem_raw[];
    const uint32_t sm = smem_u32(smem_raw);
    const int c = blockIdx.x;
    const int warp = threadIdx.x >> 5, lane = threadIdx.x & 31;
    const uint32_t bar_full = sm + SM_BAR, bar_empty = sm + SM_BAR + NSLOT * 8, bar_sig = sm + SM_BAR + NSLOT * 16;

    if (warp == 0) {
        if (lane == 0) {
            TSTAMP(0);
#pragma unroll
            for (int i = 0; i < NSLOT; i++) {
                mbar_init(bar_full + i * 8, 1);
                mbar_init(bar_empty + i * 8, 4);
            }
            mbar_init(bar_sig, 4);
            mbar_init(bar_sig + 8, 4);
            mbar_init(bar_sig + 16, 4);
            asm volatile("fence.mbarrier_init.release.cluster;" ::: "memory");
            asm volatile("fence.proxy.async.shared::cta;" ::: "memory");
        }
        __syncwarp();
        bar_arrive(1, NTHREADS);
        if (lane == 0) {
            uint64_t pol;
            asm volatile("createpolicy.fractional.L2::evict_first.b64 %0, 1.0;" : "=l"(pol));
            int slot = 0, ph = 0;
            int wslot = 0, wph = 0;
#pragma unroll 1
            for (int i = 0; i < NCHUNK; i++) {
                int tmi, x0, y0, dx = 0, dy = 64, nbox = 2;
                if (i < 2) {
                    tmi = 0; x0 = 64 * (c & 31); y0 = 256 * (c >> 5) + 128 * i;
                } else if (i < 6) {
                    int j = i - 2;
                    tmi = 1; x0 = 128 * (c & 31) + 64 * (j >> 1); y0 = 256 * (c >> 5) + 128 * (j & 1);
                } else if (i < 9) {
                    tmi = 0; x0 = 2048 + 192 * (c & 15) + 64 * (i - 6); y0 = 128 * (c >> 4);
                } else if (i < 17) {
                    int j = i - 9;
                    tmi = 2 + (j >> 2); x0 = 0; dx = 64; dy = 0;
                    y0 = (c >> 4) * SK + (SK - WIN) + 256 * (c & 15) + 64 * (j & 3);
                } else if (i < 21) {
                    tmi = 4; x0 = 256 * (c & 3) + 64 * (i - 17); y0 = 128 * (c >> 2);
                } else if (i < 29) {
                    if (c < 56) { tmi = 5; x0 = 64 * c; }
                    else if (c < 112) { tmi = 6; x0 = 64 * (c - 56); }
                    else { tmi = 0; x0 = 5120 + 64 * (c - 112); }
                    y0 = 128 * (i - 21);
                } else {
                    tmi = 7; x0 = 64 * (c & 15); y0 = 448 * (c >> 4) + 128 * (i - 29);
                    if (i == NCHUNK - 1) nbox = 1;
                }
                if (i >= NSLOT) mbar_wait(bar_empty + slot * 8, ph ^ 1);
                if (i >= INFLIGHT) {
                    mbar_wait(bar_full + wslot * 8, wph);
                    if (++wslot == NSLOT) { wslot = 0; wph ^= 1; }
                }
                const uint32_t fb = bar_full + slot * 8, dst = sm + slot * SLOT_BYTES;
                mbar_expect(fb, nbox * BOX_BYTES);
                tma2d(dst, &prm.tm[tmi], x0, y0, fb, pol);
                if (nbox == 2) tma2d(dst + BOX_BYTES, &prm.tm[tmi], x0 + dx, y0 + dy, fb, pol);
                if (++slot == NSLOT) { slot = 0; ph ^= 1; }
            }
            TSTAMP(1);
        }
        return;
    }

    unsigned epoch;
    asm volatile("ld.relaxed.gpu.global.u32 %0, [%1];" : "=r"(epoch) : "l"(&g_epoch[c * 8]) : "memory");
    float* const scr = g_scr;

    if (warp == 5) {
        const int pg = lane >> 2, q = lane & 3;
        const int col = 8 * c + 2 * q;
        float base[4], gate[4];
        {
            uint32_t w0 = *reinterpret_cast<const uint32_t*>(prm.x + col);
            uint32_t w1 = *reinterpret_cast<const uint32_t*>(prm.x + 1024 + col);
            base[0] = bflo(w0); base[1] = bflo(w1); base[2] = bfhi(w0); base[3] = bfhi(w1);
        }
        bar_sync(1, NTHREADS);
        const uint32_t tag = (epoch + 1) & 1;
        mbar_wait(bar_sig, 0);
        {
            uint4 v[3];
            int n = 0;
            while (true) {
                uint32_t bad = 0;
#pragma unroll
                for (int w = 0; w < 3; w++) {
                    v[w] = ldp4(scr + OFF_P1B + pg * 6144 + (w * 1024 + col) * 2);
                    bad |= bad4(v[w], tag);
                }
                if (!__any_sync(0xffffffffu, bad)) break;
                backoff(n);
            }
            float s[3][4];
#pragma unroll
            for (int w = 0; w < 3; w++) {
                s[w][0] = untag(v[w].x); s[w][1] = untag(v[w].y); s[w][2] = untag(v[w].z); s[w][3] = untag(v[w].w);
#pragma unroll
                for (int e = 0; e < 4; e++) {
                    float t = s[w][e];
                    t += __shfl_xor_sync(0xffffffffu, t, 4);
                    t += __shfl_xor_sync(0xffffffffu, t, 8);
                    t += __shfl_xor_sync(0xffffffffu, t, 16);
                    s[w][e] = bf16r(t);
                }
            }
#pragma unroll
            for (int e = 0; e < 4; e++) gate[e] = s[0][e];
            if (pg < 2) {
                float c1a = bf16r(1.0f + (pg ? s[2][2] : s[2][0])), c1b = bf16r(1.0f + (pg ? s[2][3] : s[2][1]));
                float sa = pg ? s[1][2] : s[1][0], sb = pg ? s[1][3] : s[1][1];
                stp4(scr + OFF_CS + (col + pg) * 4, tagf(c1a, tag), tagf(sa, tag), tagf(c1b, tag), tagf(sb, tag));
            }
        }
#pragma unroll 1
        for (int it = 0; it < 2; it++) {
            const float* src = scr + (it ? OFF_P6 + pg * 2048 : OFF_P4 + pg * 4 * 2048) + col * 2;
            const int np = it ? 1 : 4;
            mbar_wait(bar_sig + 8 + it * 8, 0);
            if (it) {
                uint4 g;
                int n = 0;
                while (true) {
                    g = ldp4(scr + OFF_GU + (7168 + col) * 2);
                    if (!__any_sync(0xffffffffu, bad4(g, tag))) break;
                    backoff(n);
                }
                gate[0] = bf16r(untag(g.x)); gate[1] = bf16r(untag(g.y));
                gate[2] = bf16r(untag(g.z)); gate[3] = bf16r(untag(g.w));
            }
            uint4 v[4];
            int n = 0;
            while (true) {
                uint32_t bad = 0;
#pragma unroll
                for (int j = 0; j < 4; j++) {
                    if (j < np) {
                        v[j] = ldp4(src + j * 2048);
                        bad |= bad4(v[j], tag);
                    } else {
                        v[j] = make_uint4(0, 0, 0, 0);
                    }
                }
                if (!__any_sync(0xffffffffu, bad)) break;
                backoff(n);
            }
            float s[4];
            s[0] = (untag(v[0].x) + untag(v[1].x)) + (untag(v[2].x) + untag(v[3].x));
            s[1] = (untag(v[0].y) + untag(v[1].y)) + (untag(v[2].y) + untag(v[3].y));
            s[2] = (untag(v[0].z) + untag(v[1].z)) + (untag(v[2].z) + untag(v[3].z));
            s[3] = (untag(v[0].w) + untag(v[1].w)) + (untag(v[2].w) + untag(v[3].w));
#pragma unroll
            for (int e = 0; e < 4; e++) {
                float t = s[e];
                t += __shfl_xor_sync(0xffffffffu, t, 4);
                t += __shfl_xor_sync(0xffffffffu, t, 8);
                t += __shfl_xor_sync(0xffffffffu, t, 16);
                base[e] = bf16r(base[e] + bf16r(gate[e] * bf16r(t)));
            }
            if (it == 0) {
                if (pg == 0)
                    stp4(scr + OFF_X1 + col * 2, tagf(base[0], tag), tagf(base[1], tag), tagf(base[2], tag),
                         tagf(base[3], tag));
                TSTAMP(40);
            } else {
                if (pg < 2) {
                    uint32_t w = pg ? pack2(base[1], base[3]) : pack2(base[0], base[2]);
                    *reinterpret_cast<uint32_t*>(prm.out + pg * 1024 + col) = w;
                }
                if (lane == 0) g_epoch[c * 8] = epoch + 1;
                TSTAMP(41);
            }
        }
        return;
    }

    const int cw = warp - 1;
    const int ti = threadIdx.x - 32;
    const int g = lane >> 2, t = lane & 3;
    const uint32_t red = sm + SM_RED;

    float xk[4];
    float m0, m1, d0, d1;
    {
        const int blk = ti >> 2, tt = ti & 3;
        uint32_t cwd[2][4], xwd[2][4];
#pragma unroll
        for (int b = 0; b < 2; b++)
#pragma unroll
            for (int j = 0; j < 4; j++) {
                cwd[b][j] = *reinterpret_cast<const uint32_t*>(prm.c + b * 1024 + 32 * blk + 8 * j + 2 * tt);
                xwd[b][j] = *reinterpret_cast<const uint32_t*>(prm.x + b * 1024 + 32 * blk + 8 * j + 2 * tt);
            }
        {
            const int k = 256 * (c >> 5) + 32 * (ti >> 4) + 8 * (ti & 3) + 2 * ((ti >> 2) & 3);
            uint32_t w0 = *reinterpret_cast<const uint32_t*>(prm.x + k);
            uint32_t w1 = *reinterpret_cast<const uint32_t*>(prm.x + 1024 + k);
            xk[0] = bflo(w0); xk[1] = bflo(w1); xk[2] = bfhi(w0); xk[3] = bfhi(w1);
        }
        bar_sync(1, NTHREADS);
#pragma unroll
        for (int b = 0; b < 2; b++) {
            uint32_t o[4];
#pragma unroll
            for (int j = 0; j < 4; j++) o[j] = pack2(silu_f(bflo(cwd[b][j])), silu_f(bfhi(cwd[b][j])));
            sts128(sm + SM_SILU + blk * 128 + b * 64 + tt * 16, o[0], o[1], o[2], o[3]);
        }
        float v0[8], v1[8];
#pragma unroll
        for (int j = 0; j < 4; j++) {
            v0[2 * j] = bflo(xwd[0][j]); v0[2 * j + 1] = bfhi(xwd[0][j]);
            v1[2 * j] = bflo(xwd[1][j]); v1[2 * j + 1] = bfhi(xwd[1][j]);
        }
        ln_stats(v0, v1, red, cw, lane, m0, m1, d0, d1);
    }
    const uint32_t tag = (epoch + 1) & 1;
    TSTAMP_W(2, 1);

    const int mi = lane >> 3, r8 = lane & 7;
    const uint32_t gemvA = (uint32_t)(((mi >> 1) * 8 + r8) * 128 + (((cw * 2 + (mi & 1)) ^ r8) << 4));
    const uint32_t pvA0 = (uint32_t)((cw >> 1) * BOX_BYTES + ((mi >> 1) * 8 + r8) * 128 +
                                     (((((cw & 1) * 2 + 0) * 2 + (mi & 1)) ^ r8) << 4));
    const uint32_t pvA1 = (uint32_t)((cw >> 1) * BOX_BYTES + ((mi >> 1) * 8 + r8) * 128 +
                                     (((((cw & 1) * 2 + 1) * 2 + (mi & 1)) ^ r8) << 4));

    int slot = 0, ph = 0;
    float lsum0 = 0.f, lsum1 = 0.f, mx0 = 0.f, mx1 = 0.f;

#pragma unroll 1
    for (int job = 0; job < 13; job++) {
        int nch = 1;
        uint32_t act = 0;
        float* outp = nullptr;
        int cs = 2, bs = 1;
        bool pv = false;
        if (job == 0) {
            nch = 2;
            act = sm + SM_SILU + (c >> 5) * 1024;
            outp = scr + OFF_P1 + (c >> 5) * 4096 + (c & 31) * 128;
        } else if (job <= 2) {
            if (job == 1) {
                const int kl = 32 * (ti >> 4) + 8 * (ti & 3) + 2 * ((ti >> 2) & 3);
                const float* src = scr + OFF_P1 + (256 * (c >> 5) + kl) * 2;
                uint4 v[8];
                int n = 0;
                while (true) {
                    uint32_t bad = 0;
#pragma unroll
                    for (int p = 0; p < 4; p++) {
                        v[p] = ldp4(src + p * 4096);
                        v[4 + p] = ldp4(src + p * 4096 + 2048);
                    }
#pragma unroll
                    for (int p = 0; p < 8; p++) bad |= bad4(v[p], tag);
                    if (!bad) break;
                    backoff(n);
                }
                float sa[4], ca[4];
                sa[0] = (untag(v[0].x) + untag(v[1].x)) + (untag(v[2].x) + untag(v[3].x));
                sa[1] = (untag(v[0].y) + untag(v[1].y)) + (untag(v[2].y) + untag(v[3].y));
                sa[2] = (untag(v[0].z) + untag(v[1].z)) + (untag(v[2].z) + untag(v[3].z));
                sa[3] = (untag(v[0].w) + untag(v[1].w)) + (untag(v[2].w) + untag(v[3].w));
                ca[0] = (untag(v[4].x) + untag(v[5].x)) + (untag(v[6].x) + untag(v[7].x));
                ca[1] = (untag(v[4].y) + untag(v[5].y)) + (untag(v[6].y) + untag(v[7].y));
                ca[2] = (untag(v[4].z) + untag(v[5].z)) + (untag(v[6].z) + untag(v[7].z));
                ca[3] = (untag(v[4].w) + untag(v[5].w)) + (untag(v[6].w) + untag(v[7].w));
                float h[4];
#pragma unroll
                for (int e = 0; e < 4; e++)
                    h[e] = modulate(xk[e], (e & 1) ? m1 : m0, (e & 1) ? d1 : d0, bf16r(1.0f + bf16r(ca[e])), bf16r(sa[e]));
                const uint32_t dst = sm + SM_H + (ti >> 4) * 128 + (ti & 15) * 4;
                sts32(dst, pack2(h[0], h[2]));
                sts32(dst + 64, pack2(h[1], h[3]));
                bar_sync(2, 128);
                TSTAMP_W(3, 1);
            }
            nch = 2;
            act = sm + SM_H;
            outp = scr + OFF_P2 + (c >> 5) * 8192 + 128 * (c & 31) + 64 * (job - 1);
            cs = 1; bs = 4096;
        } else if (job <= 5) {
            act = sm + SM_SILU + (c >> 4) * 512;
            outp = scr + OFF_P1B + (c >> 4) * 6144 + (192 * (c & 15) + 64 * (job - 3)) * 2;
        } else if (job == 6) {
            if (lane == 0) mbar_arrive(bar_sig);
            const int bh = c >> 4;
            {
                const float* src = scr + OFF_P2 + (bh >> 2) * 4096 + (bh & 3) * 1024 + ti * 8;
                uint4 v[8];
                int n = 0;
                while (true) {
                    uint32_t bad = 0;
#pragma unroll
                    for (int p = 0; p < 4; p++) {
                        v[2 * p] = ldp4(src + p * 8192);
                        v[2 * p + 1] = ldp4(src + p * 8192 + 4);
                    }
#pragma unroll
                    for (int p = 0; p < 8; p++) bad |= bad4(v[p], tag);
                    if (!bad) break;
                    backoff(n);
                }
                float qv[8];
                qv[0] = (untag(v[0].x) + untag(v[2].x)) + (untag(v[4].x) + untag(v[6].x));
                qv[1] = (untag(v[0].y) + untag(v[2].y)) + (untag(v[4].y) + untag(v[6].y));
                qv[2] = (untag(v[0].z) + untag(v[2].z)) + (untag(v[4].z) + untag(v[6].z));
                qv[3] = (untag(v[0].w) + untag(v[2].w)) + (untag(v[4].w) + untag(v[6].w));
                qv[4] = (untag(v[1].x) + untag(v[3].x)) + (untag(v[5].x) + untag(v[7].x));
                qv[5] = (untag(v[1].y) + untag(v[3].y)) + (untag(v[5].y) + untag(v[7].y));
                qv[6] = (untag(v[1].z) + untag(v[3].z)) + (untag(v[5].z) + untag(v[7].z));
                qv[7] = (untag(v[1].w) + untag(v[3].w)) + (untag(v[5].w) + untag(v[7].w));
                const int head = ti >> 4, dq = ti & 15;
                const uint32_t dst = sm + SM_Q + (dq >> 2) * 512 + head * 64 + (dq & 3) * 4;
#pragma unroll
                for (int u = 0; u < 4; u++) sts32(dst + u * 16, pack2(qv[2 * u], qv[2 * u + 1]));
            }
            bar_sync(2, 128);
            TSTAMP_W(4, 1);
            uint4 qf[4];
#pragma unroll
            for (int p = 0; p < 4; p++) qf[p] = lds128(sm + SM_Q + p * 512 + g * 64 + t * 16);
            float sc[4][4];
            const uint32_t kA = (uint32_t)((cw * 16 + (mi & 1) * 8 + r8) * 128);
#pragma unroll
            for (int j = 0; j < 4; j++) {
                mbar_wait(bar_full + slot * 8, ph);
                const uint32_t sb = sm + slot * SLOT_BYTES + kA;
                uint32_t a[8][4];
#pragma unroll
                for (int i = 0; i < 8; i++)
                    ldsm4(a[i], sb + (i >> 2) * BOX_BYTES + ((((i & 3) * 2 + (mi >> 1)) ^ r8) << 4));
                float e0[4] = {0.f, 0.f, 0.f, 0.f}, e1[4] = {0.f, 0.f, 0.f, 0.f};
#pragma unroll
                for (int p = 0; p < 4; p++) {
                    mma16816(e0, a[2 * p], qf[p].x, qf[p].y);
                    mma16816(e1, a[2 * p + 1], qf[p].z, qf[p].w);
                }
                __syncwarp();
                if (lane == 0) mbar_arrive(bar_empty + slot * 8);
                if (++slot == NSLOT) { slot = 0; ph ^= 1; }
#pragma unroll
                for (int e = 0; e < 4; e++) sc[j][e] = bf16r(bf16r(e0[e] + e1[e]) * 0.08838834764831845f);
            }
            float a0 = fmaxf(fmaxf(sc[0][0], sc[0][2]), fmaxf(sc[1][0], sc[1][2]));
            a0 = fmaxf(a0, fmaxf(fmaxf(sc[2][0], sc[2][2]), fmaxf(sc[3][0], sc[3][2])));
            float a1 = fmaxf(fmaxf(sc[0][1], sc[0][3]), fmaxf(sc[1][1], sc[1][3]));
            a1 = fmaxf(a1, fmaxf(fmaxf(sc[2][1], sc[2][3]), fmaxf(sc[3][1], sc[3][3])));
#pragma unroll
            for (int o = 4; o < 32; o <<= 1) {
                a0 = fmaxf(a0, __shfl_xor_sync(0xffffffffu, a0, o));
                a1 = fmaxf(a1, __shfl_xor_sync(0xffffffffu, a1, o));
            }
            if (g == 0) {
                stsf(red + 64 + cw * 32 + t * 8, a0);
                stsf(red + 64 + cw * 32 + t * 8 + 4, a1);
            }
            bar_sync(2, 128);
#pragma unroll
            for (int w = 0; w < 4; w++) {
                a0 = fmaxf(a0, ldsf(red + 64 + w * 32 + t * 8));
                a1 = fmaxf(a1, ldsf(red + 64 + w * 32 + t * 8 + 4));
            }
            mx0 = a0; mx1 = a1;
            float l0 = 0.f, l1 = 0.f;
#pragma unroll
            for (int j = 0; j < 4; j++) {
                const uint32_t dst = sm + SM_P + (2 * j + (cw >> 1)) * 512 + (g >> 1) * 16 + (cw & 1) * 8 + (g & 1) * 2;
#pragma unroll
                for (int e = 0; e < 4; e++) {
                    float p = __expf(sc[j][e] - ((e & 1) ? a1 : a0));
                    if (e & 1) l1 += p; else l0 += p;
                    __nv_bfloat16 pb = __float2bfloat16_rn(p);
                    sts16(dst + (2 * t + (e & 1)) * 64 + (e >> 1) * 4, *reinterpret_cast<uint16_t*>(&pb));
                }
            }
#pragma unroll
            for (int o = 4; o < 32; o <<= 1) {
                l0 += __shfl_xor_sync(0xffffffffu, l0, o);
                l1 += __shfl_xor_sync(0xffffffffu, l1, o);
            }
            if (g == 0) {
                stsf(red + 192 + cw * 32 + t * 8, l0);
                stsf(red + 192 + cw * 32 + t * 8 + 4, l1);
            }
            bar_sync(2, 128);
            lsum0 = (ldsf(red + 192 + t * 8) + ldsf(red + 224 + t * 8)) + (ldsf(red + 256 + t * 8) + ldsf(red + 288 + t * 8));
            lsum1 = (ldsf(red + 196 + t * 8) + ldsf(red + 228 + t * 8)) + (ldsf(red + 260 + t * 8) + ldsf(red + 292 + t * 8));
            TSTAMP_W(5, 1);
            nch = 4;
            act = sm + SM_P;
            pv = true;
        } else if (job <= 10) {
            if (job == 7) {
                const int b = ti >> 6, p = ti & 63;
                const int d = 32 * (p >> 4) + 8 * (p & 3) + 2 * ((p >> 2) & 3);
                const int hb = (b * 32 + (c >> 2)) * 16;
                uint2 ml;
                int n = 0;
                while (true) {
                    ml = ldp2(scr + OFF_ML + (hb + (lane & 15)) * 2);
                    if (!__any_sync(0xffffffffu, bad2(ml, tag))) break;
                    backoff(n);
                }
                uint2 v[16];
                while (true) {
                    uint32_t bad = 0;
#pragma unroll
                    for (int s = 0; s < 16; s++) v[s] = ldp2(scr + OFF_P3 + (hb + s) * 128 + d);
#pragma unroll
                    for (int s = 0; s < 16; s++) bad |= bad2(v[s], tag);
                    if (!bad) break;
                    backoff(n);
                }
                const float ms = untag(ml.x);
                float M = ms;
#pragma unroll
                for (int o = 1; o < 16; o <<= 1) M = fmaxf(M, __shfl_xor_sync(0xffffffffu, M, o));
                const float w = __expf(ms - M);
                float L = w * untag(ml.y);
#pragma unroll
                for (int o = 1; o < 16; o <<= 1) L += __shfl_xor_sync(0xffffffffu, L, o);
                float o0 = 0.f, o1 = 0.f;
#pragma unroll
                for (int s = 0; s < 16; s++) {
                    const float ws = __shfl_sync(0xffffffffu, w, s);
                    o0 += ws * untag(v[s].x);
                    o1 += ws * untag(v[s].y);
                }
                const float inv = 1.0f / L;
                sts32(sm + SM_O + (p >> 4) * 128 + b * 64 + (p & 15) * 4, pack2(o0 * inv, o1 * inv));
                bar_sync(2, 128);
                TSTAMP_W(7, 1);
            }
            act = sm + SM_O;
            outp = scr + OFF_P4 + (c >> 2) * 2048 + (256 * (c & 3) + 64 * (job - 7)) * 2;
        } else if (job == 11) {
            if (lane == 0) mbar_arrive(bar_sig + 8);
            TSTAMP_W(8, 1);
            nch = 8;
            outp = scr + OFF_GU + c * 128;
            if (c < 112) {
                const int blk = ti >> 2, tt = ti & 3;
                const int k0 = 32 * blk + 2 * tt;
                uint32_t c1p[2][4], sbp[2][4];
                int n = 0;
                {
                    uint4 v[8];
                    while (true) {
                        uint32_t bad = 0;
#pragma unroll
                        for (int j = 0; j < 4; j++) {
                            v[2 * j] = ldp4(scr + OFF_CS + (k0 + 8 * j) * 4);
                            v[2 * j + 1] = ldp4(scr + OFF_CS + (k0 + 8 * j) * 4 + 4);
                        }
#pragma unroll
                        for (int j = 0; j < 8; j++) bad |= bad4(v[j], tag);
                        if (!bad) break;
                        backoff(n);
                    }
#pragma unroll
                    for (int j = 0; j < 4; j++) {
                        c1p[0][j] = __byte_perm(v[2 * j].x, v[2 * j + 1].x, 0x7632);
                        sbp[0][j] = __byte_perm(v[2 * j].y, v[2 * j + 1].y, 0x7632);
                        c1p[1][j] = __byte_perm(v[2 * j].z, v[2 * j + 1].z, 0x7632);
                        sbp[1][j] = __byte_perm(v[2 * j].w, v[2 * j + 1].w, 0x7632);
                    }
                }
                uint4 xv[4];
                while (true) {
                    uint32_t bad = 0;
#pragma unroll
                    for (int j = 0; j < 4; j++) xv[j] = ldp4(scr + OFF_X1 + (k0 + 8 * j) * 2);
#pragma unroll
                    for (int j = 0; j < 4; j++) bad |= bad4(xv[j], tag);
                    if (!bad) break;
                    backoff(n);
                }
                float v0[8], v1[8];
#pragma unroll
                for (int j = 0; j < 4; j++) {
                    v0[2 * j] = untag(xv[j].x); v1[2 * j] = untag(xv[j].y);
                    v0[2 * j + 1] = untag(xv[j].z); v1[2 * j + 1] = untag(xv[j].w);
                }
                float n0, n1, e0, e1;
                ln_stats(v0, v1, red + 320, cw, lane, n0, n1, e0, e1);
                uint32_t o0[4], o1[4];
#pragma unroll
                for (int j = 0; j < 4; j++) {
                    o0[j] = pack2(modulate(v0[2 * j], n0, e0, bflo(c1p[0][j]), bflo(sbp[0][j])),
                                  modulate(v0[2 * j + 1], n0, e0, bfhi(c1p[0][j]), bfhi(sbp[0][j])));
                    o1[j] = pack2(modulate(v1[2 * j], n1, e1, bflo(c1p[1][j]), bflo(sbp[1][j])),
                                  modulate(v1[2 * j + 1], n1, e1, bfhi(c1p[1][j]), bfhi(sbp[1][j])));
                }
                sts128(sm + SM_H2 + blk * 128 + tt * 16, o0[0], o0[1], o0[2], o0[3]);
                sts128(sm + SM_H2 + blk * 128 + 64 + tt * 16, o1[0], o1[1], o1[2], o1[3]);
                bar_sync(2, 128);
                act = sm + SM_H2;
            } else {
                act = sm + SM_SILU;
            }
            TSTAMP_W(9, 1);
        } else {
            if (lane == 0) mbar_arrive(bar_sig + 16);
            TSTAMP_W(10, 1);
            const int p0 = ti, p1 = ti + 128;
            const int f0 = 448 * (c >> 4) + 32 * (p0 >> 4) + 8 * (p0 & 3) + 2 * ((p0 >> 2) & 3);
            const bool two = p1 < 224;
            const float* gsrc = scr + OFF_GU + f0 * 2;
            uint4 v[4];
            int n = 0;
            while (true) {
                v[0] = ldp4(gsrc);
                v[1] = ldp4(gsrc + 7168);
                uint32_t bad = bad4(v[0], tag) | bad4(v[1], tag);
                if (two) {
                    v[2] = ldp4(gsrc + 512);
                    v[3] = ldp4(gsrc + 512 + 7168);
                    bad |= bad4(v[2], tag) | bad4(v[3], tag);
                }
                if (!bad) break;
                backoff(n);
            }
#pragma unroll
            for (int u = 0; u < 2; u++) {
                if (u == 0 || two) {
                    const uint4 gt = v[2 * u], up = v[2 * u + 1];
                    const float h0 = bf16r(silu_f(bf16r(untag(gt.x)))) * bf16r(untag(up.x));
                    const float h1 = bf16r(silu_f(bf16r(untag(gt.y)))) * bf16r(untag(up.y));
                    const float h2 = bf16r(silu_f(bf16r(untag(gt.z)))) * bf16r(untag(up.z));
                    const float h3 = bf16r(silu_f(bf16r(untag(gt.w)))) * bf16r(untag(up.w));
                    const uint32_t dst = sm + SM_HH + ((ti >> 4) + 8 * u) * 128 + (ti & 15) * 4;
                    sts32(dst, pack2(h0, h2));
                    sts32(dst + 64, pack2(h1, h3));
                }
            }
            bar_sync(2, 128);
            TSTAMP_W(11, 1);
            nch = 4;
            act = sm + SM_HH;
            outp = scr + OFF_P6 + (c >> 4) * 2048 + (c & 15) * 128;
        }

        const uint32_t laneA0 = pv ? pvA0 : gemvA;
        const uint32_t laneA1 = pv ? pvA1 : gemvA + BOX_BYTES;
        const uint32_t bstride = pv ? 512u : 128u;
        const uint32_t boff2 = pv ? 0u : 256u;
        const uint32_t cstride = pv ? 1024u : 512u;
        uint32_t ba = act + (pv ? g : (g & 1)) * 64 + t * 16;
        float acc[4][4];
#pragma unroll
        for (int i = 0; i < 4; i++)
#pragma unroll
            for (int e = 0; e < 4; e++) acc[i][e] = 0.f;
#pragma unroll 1
        for (int ch = 0; ch < nch; ch++) {
            const bool full = !(job == 12 && ch == 3);
            const uint4 b0 = lds128(ba), b1 = lds128(ba + bstride);
            uint4 b2, b3;
            if (full) {
                b2 = lds128(ba + boff2);
                b3 = lds128(ba + boff2 + bstride);
            }
            mbar_wait(bar_full + slot * 8, ph);
            const uint32_t sb = sm + slot * SLOT_BYTES;
            uint32_t a[8][4];
#pragma unroll
            for (int i = 0; i < 4; i++) ldsm4t(a[i], sb + laneA0 + i * 2048);
            if (full) {
#pragma unroll
                for (int i = 0; i < 4; i++) ldsm4t(a[4 + i], sb + laneA1 + i * 2048);
            }
            mma16816(acc[0], a[0], b0.x, b0.y);
            mma16816(acc[1], a[1], b0.z, b0.w);
            mma16816(acc[0], a[2], b1.x, b1.y);
            mma16816(acc[1], a[3], b1.z, b1.w);
            if (full) {
                mma16816(acc[2], a[4], b2.x, b2.y);
                mma16816(acc[3], a[5], b2.z, b2.w);
                mma16816(acc[2], a[6], b3.x, b3.y);
                mma16816(acc[3], a[7], b3.z, b3.w);
            }
            __syncwarp();
            if (lane == 0) mbar_arrive(bar_empty + slot * 8);
            if (++slot == NSLOT) { slot = 0; ph ^= 1; }
            ba += cstride;
        }
        if (!pv) {
            float r[4];
#pragma unroll
            for (int e = 0; e < 4; e++) r[e] = (acc[0][e] + acc[1][e]) + (acc[2][e] + acc[3][e]);
            const float v = (t & 2) ? ((t & 1) ? r[3] : r[2]) : ((t & 1) ? r[1] : r[0]);
            stp1(outp + (cw * 16 + g + (t >> 1) * 8) * cs + (t & 1) * bs, tagf(v, tag));
        } else {
            const int bh = c >> 4, sp = c & 15;
            const int h0 = (bh >> 2) * 32 + (bh & 3) * 8 + 2 * t;
            float* o0 = scr + OFF_P3 + (h0 * 16 + sp) * 128 + cw * 32 + g;
            float* o1 = o0 + 16 * 128;
#pragma unroll
            for (int u = 0; u < 2; u++) {
                stp1(o0 + u * 16, tagf(acc[2 * u][0] + acc[2 * u + 1][0], tag));
                stp1(o1 + u * 16, tagf(acc[2 * u][1] + acc[2 * u + 1][1], tag));
                stp1(o0 + u * 16 + 8, tagf(acc[2 * u][2] + acc[2 * u + 1][2], tag));
                stp1(o1 + u * 16 + 8, tagf(acc[2 * u][3] + acc[2 * u + 1][3], tag));
            }
            if (cw == 3 && g == 0) {
                stp2(scr + OFF_ML + (h0 * 16 + sp) * 2, tagf(mx0, tag), tagf(lsum0, tag));
                stp2(scr + OFF_ML + ((h0 + 1) * 16 + sp) * 2, tagf(mx1, tag), tagf(lsum1, tag));
            }
            TSTAMP_W(6, 1);
        }
    }
    TSTAMP_W(12, 1);
}

typedef CUresult (*EncodeFn)(CUtensorMap*, CUtensorMapDataType, cuuint32_t, void*, const cuuint64_t*, const cuuint64_t*,
                             const cuuint32_t*, const cuuint32_t*, CUtensorMapInterleave, CUtensorMapSwizzle,
                             CUtensorMapL2promotion, CUtensorMapFloatOOBfill);

void make_map(EncodeFn enc, CUtensorMap* tm, const void* base, uint64_t cols, uint64_t rows) {
    cuuint64_t gd[2] = {cols, rows};
    cuuint64_t gs[1] = {cols * 2};
    cuuint32_t bd[2] = {64, 64};
    cuuint32_t es[2] = {1, 1};
    enc(tm, CU_TENSOR_MAP_DATA_TYPE_BFLOAT16, 2, const_cast<void*>(base), gd, gs, bd, es, CU_TENSOR_MAP_INTERLEAVE_NONE,
        CU_TENSOR_MAP_SWIZZLE_128B, CU_TENSOR_MAP_L2_PROMOTION_L2_256B, CU_TENSOR_MAP_FLOAT_OOB_FILL_NONE);
}

}

extern "C" void kernel_launch(void* const* d_in, const int* in_sizes, int n_in, void* d_out, int out_size) {
    static EncodeFn enc = nullptr;
    if (!enc) {
        cudaDriverEntryPointQueryResult qr;
        cudaGetDriverEntryPoint("cuTensorMapEncodeTiled", (void**)&enc, cudaEnableDefault, &qr);
        cudaFuncSetAttribute(fused_kernel, cudaFuncAttributeMaxDynamicSharedMemorySize, SM_TOTAL);
    }
    Params p;
    make_map(enc, &p.tm[0], d_in[10], 6144, 1024);
    make_map(enc, &p.tm[1], d_in[3], 4096, 1024);
    make_map(enc, &p.tm[2], d_in[1], 128, (uint64_t)8 * SK);
    make_map(enc, &p.tm[3], d_in[2], 128, (uint64_t)8 * SK);
    make_map(enc, &p.tm[4], d_in[4], 1024, 4096);
    make_map(enc, &p.tm[5], d_in[6], 3584, 1024);
    make_map(enc, &p.tm[6], d_in[7], 3584, 1024);
    make_map(enc, &p.tm[7], d_in[8], 1024, 3584);
    p.x = (const __nv_bfloat16*)d_in[0];
    p.c = (const __nv_bfloat16*)d_in[9];
    p.out = (__nv_bfloat16*)d_out;
    fused_kernel<<<NCTA, NTHREADS, SM_TOTAL>>>(p);
}
```

```cpp
#include <cuda_runtime.h>
#include <cuda_bf16.h>
#include <cuda.h>
#include <stdint.h>

namespace {

constexpr int SK = 32768, WIN = 4096;
constexpr int NCTA = 128;
constexpr int BOX_BYTES = 8192;
constexpr int NPOS = 24;
constexpr int NBOX = 66;
constexpr int NTHREADS = 512;

constexpr int LW = 3;
constexpr int PD = 6;
constexpr int TAU = 340;
constexpr int TAU2 = 328;
constexpr int TAU3 = 420;
constexpr int TLEAD = 1100;
constexpr int LLEAD = 500;
constexpr int LAGSH = 9;
constexpr int LWX = 3;
constexpr int PDX = 2;
constexpr int BEND = 58;
constexpr int LWE = 2;
constexpr int NPF0 = 2;
constexpr int PS0 = 600, PS1 = 200, XS0 = 400, XS1 = 100;

constexpr int OFF_P1 = 0;
constexpr int OFF_P1B = OFF_P1 + 4 * 2048 * 2;
constexpr int OFF_P2 = OFF_P1B + 192 * 512;
constexpr int OFF_P3 = OFF_P2 + 4 * 2 * 4096;
constexpr int OFF_ML = OFF_P3 + 128 * 1024;
constexpr int OFF_P4 = OFF_ML + 128 * 16;
constexpr int OFF_X1 = OFF_P4 + 64 * 512;
constexpr int OFF_CS = OFF_X1 + 4 * 1024 * 2;
constexpr int OFF_GU = OFF_CS + 4 * 1024 * 4;
constexpr int OFF_P6 = OFF_GU + 8192 * 2;
constexpr int SCR_FLOATS = OFF_P6 + 64 * 1792;

__device__ __align__(1024) float g_scr[SCR_FLOATS];
__device__ __align__(32) unsigned g_epoch[NCTA * 8];

constexpr int SM_SILU = NPOS * BOX_BYTES;
constexpr int SM_H = SM_SILU + 4096;
constexpr int SM_O = SM_H + 1024;
constexpr int SM_H2 = SM_O + 1024;
constexpr int SM_HH = SM_H2 + 4096;
constexpr int SM_Q = SM_HH + 2048;
constexpr int SM_P = SM_Q + 2048;
constexpr int SM_CX = SM_P + 4096;
constexpr int SM_RED = SM_CX + 8192;
constexpr int SM_CMB = SM_RED + 1024;
constexpr int SM_WS = SM_CMB + 512;
constexpr int SM_DESC = SM_WS + 512;
constexpr int SM_BOXT = SM_DESC + 1024;
constexpr int SM_BOXT2 = SM_BOXT + 768;
constexpr int SM_FULL = SM_BOXT2 + 768;
constexpr int SM_EMPTY = SM_FULL + NPOS * 8;
constexpr int SM_PROG = SM_EMPTY + NPOS * 8;
constexpr int SM_CXB = SM_PROG + 8;
constexpr int SM_EPOCH = SM_PROG + 16;
constexpr int SM_TOTAL = SM_EPOCH + 16;

enum { BAR_INIT = 1, BAR_MMA = 2, BAR_AUX = 3,
       ACT_H = 4, ACT_Q = 5, ACT_O = 6, ACT_H2 = 7, ACT_HH = 8,
       SIG_S1 = 9, SIG_QK = 9, SIG_S2 = 10, SIG_PV = 11, SIG_WO = 12, SIG_S5 = 13,
       RS_S1B = 14, RS_WO = 15,
       RS_S5 = 0 };
enum { U_BOX0 = 1, U_BOX1 = 2, U_BOX2 = 4, U_FL0 = 8, U_FL1 = 16, U_FL2 = 32, U_FL3 = 64, U_PV = 128, U_QSTR = 256,
       U_CMB = 512, U_QK = 1024, U_LAST = 2048, U_CLR = 4096, U_LONG = 8192, U_BSTR = 16384 };

struct Params {
    const __nv_bfloat16* x;
    const __nv_bfloat16* c;
    __nv_bfloat16* out;
    float* scr;
    const __nv_bfloat16* wmod;
    unsigned* epoch;
    CUtensorMap tm[8];
};

constexpr int SPIN_LIMIT = 1 << 22;

__device__ __forceinline__ uint32_t smem_u32(const void* p) { return (uint32_t)__cvta_generic_to_shared(p); }
__device__ __forceinline__ void mbar_init(uint32_t bar, int cnt) {
    asm volatile("mbarrier.init.shared::cta.b64 [%0], %1;" ::"r"(bar), "r"(cnt) : "memory");
}
__device__ __forceinline__ void mbar_expect(uint32_t bar, uint32_t bytes) {
    asm volatile("mbarrier.arrive.expect_tx.shared::cta.b64 _, [%0], %1;" ::"r"(bar), "r"(bytes) : "memory");
}
__device__ __forceinline__ void mbar_wait(uint32_t bar, uint32_t parity) {
    asm volatile(
        "{\n"
        ".reg .pred p, q;\n"
        ".reg .u32 n;\n"
        "mov.u32 n, 0;\n"
        "WAIT_LOOP:\n"
        "mbarrier.try_wait.parity.shared::cta.b64 p, [%0], %1;\n"
        "add.u32 n, n, 1;\n"
        "setp.lt.and.u32 q, n, %2, !p;\n"
        "@q bra.uni WAIT_LOOP;\n"
        "@!p trap;\n"
        "}\n" ::"r"(bar),
        "r"(parity), "n"(SPIN_LIMIT)
        : "memory");
}
__device__ __forceinline__ void mbar_wait_soft(uint32_t bar, uint32_t parity) {
    asm volatile(
        "{\n"
        ".reg .pred p, q;\n"
        ".reg .u32 n;\n"
        "mov.u32 n, 0;\n"
        "WAIT_LOOP:\n"
        "mbarrier.try_wait.parity.shared::cta.b64 p, [%0], %1;\n"
        "add.u32 n, n, 1;\n"
        "setp.lt.and.u32 q, n, 4096, !p;\n"
        "@q bra.uni WAIT_LOOP;\n"
        "}\n" ::"r"(bar),
        "r"(parity)
        : "memory");
}
__device__ __forceinline__ uint32_t mbar_try(uint32_t bar, uint32_t parity) {
    uint32_t ok;
    asm volatile(
        "{\n.reg .pred p;\nmbarrier.test_wait.parity.shared::cta.b64 p, [%1], %2;\nselp.u32 %0, 1, 0, p;\n}"
        : "=r"(ok)
        : "r"(bar), "r"(parity)
        : "memory");
    return ok;
}
__device__ __forceinline__ void tma2d(uint32_t dst, const CUtensorMap* tm, int c0, int c1, uint32_t bar, uint64_t pol) {
    asm volatile(
        "cp.async.bulk.tensor.2d.shared::cluster.global.mbarrier::complete_tx::bytes.L2::cache_hint [%0], [%1, {%3, "
        "%4}], [%2], %5;" ::"r"(dst),
        "l"(tm), "r"(bar), "r"(c0), "r"(c1), "l"(pol)
        : "memory");
}
__device__ __forceinline__ void bulk_g2s(uint32_t dst, const void* src, uint32_t bytes, uint32_t bar) {
    asm volatile("cp.async.bulk.shared::cluster.global.mbarrier::complete_tx::bytes [%0], [%1], %2, [%3];" ::"r"(dst),
                 "l"(src), "r"(bytes), "r"(bar)
                 : "memory");
}
__device__ __forceinline__ void tma2d_prefetch(const CUtensorMap* tm, int c0, int c1, uint64_t pol) {
    asm volatile("cp.async.bulk.prefetch.tensor.2d.L2.global.L2::cache_hint [%0, {%1, %2}], %3;" ::"l"(tm), "r"(c0), "r"(c1),
                 "l"(pol)
                 : "memory");
}
__device__ __forceinline__ void bar_sync(int id, int n) { asm volatile("bar.sync %0, %1;" ::"r"(id), "r"(n) : "memory"); }
__device__ __forceinline__ void bar_arrive(int id, int n) { asm volatile("bar.arrive %0, %1;" ::"r"(id), "r"(n) : "memory"); }

__device__ __forceinline__ void ldp4_if(uint4& v, const float* p, uint32_t cond) {
    asm volatile("{\n.reg .pred q;\nsetp.ne.u32 q, %5, 0;\n@q ld.relaxed.gpu.global.v4.u32 {%0,%1,%2,%3}, [%4];\n}"
                 : "+r"(v.x), "+r"(v.y), "+r"(v.z), "+r"(v.w)
                 : "l"(p), "r"(cond)
                 : "memory");
}
__device__ __forceinline__ void stp1(float* p, uint32_t v) {
    asm volatile("st.relaxed.gpu.global.u32 [%0], %1;" ::"l"(p), "r"(v) : "memory");
}
__device__ __forceinline__ void stp1_if(float* p, uint32_t v, uint32_t cond) {
    asm volatile("{\n.reg .pred q;\nsetp.ne.u32 q, %2, 0;\n@q st.relaxed.gpu.global.u32 [%0], %1;\n}" ::"l"(p), "r"(v), "r"(cond) : "memory");
}
__device__ __forceinline__ void mbar_arrive_if(uint32_t bar, uint32_t cond) {
    asm volatile("{\n.reg .pred q;\nsetp.ne.u32 q, %1, 0;\n@q mbarrier.arrive.shared::cta.b64 _, [%0];\n}" ::"r"(bar), "r"(cond) : "memory");
}
__device__ __forceinline__ void bar_arrive_if(int id, int n, uint32_t cond) {
    asm volatile("{\n.reg .pred q;\nsetp.ne.u32 q, %2, 0;\n@q bar.arrive %0, %1;\n}" ::"r"(id), "r"(n), "r"(cond) : "memory");
}
__device__ __forceinline__ void stp4(float* p, uint32_t a, uint32_t b, uint32_t c, uint32_t d) {
    asm volatile("st.relaxed.gpu.global.v4.u32 [%0], {%1,%2,%3,%4};" ::"l"(p), "r"(a), "r"(b), "r"(c), "r"(d) : "memory");
}
__device__ __forceinline__ uint32_t tagf(float v, uint32_t tag) { return (__float_as_uint(v) & ~3u) | tag; }
__device__ __forceinline__ float untag(uint32_t v) { return __uint_as_float(v & ~3u); }
__device__ __forceinline__ uint32_t and4(const uint4& v) { return v.x & v.y & v.z & v.w; }
__device__ __forceinline__ void spin_check(int& n) {
    if (++n > SPIN_LIMIT) __trap();
}
__device__ __forceinline__ float bf16r(float x) { return __bfloat162float(__float2bfloat16_rn(x)); }
__device__ __forceinline__ uint32_t pack2(float lo, float hi) {
    __nv_bfloat162 v = __floats2bfloat162_rn(lo, hi);
    return *reinterpret_cast<uint32_t*>(&v);
}
__device__ __forceinline__ float bflo(uint32_t w) { return __uint_as_float(w << 16); }
__device__ __forceinline__ float bfhi(uint32_t w) { return __uint_as_float(w & 0xffff0000u); }
__device__ __forceinline__ float ex2(float x) {
    float r;
    asm("ex2.approx.ftz.f32 %0, %1;" : "=f"(r) : "f"(x));
    return r;
}
__device__ __forceinline__ float rcp(float x) {
    float r;
    asm("rcp.approx.ftz.f32 %0, %1;" : "=f"(r) : "f"(x));
    return r;
}
constexpr float LOG2E = 1.4426950408889634f;
__device__ __forceinline__ float exp_f(float x) { return ex2(x * LOG2E); }
__device__ __forceinline__ float silu_f(float x) { return x * rcp(1.0f + ex2(x * -LOG2E)); }
__device__ __forceinline__ float sqrt_fast(float x) {
    float r;
    asm("sqrt.approx.f32 %0, %1;" : "=f"(r) : "f"(x));
    return r;
}

__device__ __forceinline__ void ldsm4t(uint32_t (&a)[4], uint32_t addr) {
    asm volatile("ldmatrix.sync.aligned.m8n8.x4.trans.shared.b16 {%0,%1,%2,%3}, [%4];"
                 : "=r"(a[0]), "=r"(a[1]), "=r"(a[2]), "=r"(a[3])
                 : "r"(addr)
                 : "memory");
}
__device__ __forceinline__ void ldsm4(uint32_t (&a)[4], uint32_t addr) {
    asm volatile("ldmatrix.sync.aligned.m8n8.x4.shared.b16 {%0,%1,%2,%3}, [%4];"
                 : "=r"(a[0]), "=r"(a[1]), "=r"(a[2]), "=r"(a[3])
                 : "r"(addr)
                 : "memory");
}
__device__ __forceinline__ void mma16816(float (&d)[4], const uint32_t (&a)[4], uint32_t b0, uint32_t b1) {
    asm volatile(
        "mma.sync.aligned.m16n8k16.row.col.f32.bf16.bf16.f32 {%0,%1,%2,%3}, {%4,%5,%6,%7}, {%8,%9}, {%0,%1,%2,%3};"
        : "+f"(d[0]), "+f"(d[1]), "+f"(d[2]), "+f"(d[3])
        : "r"(a[0]), "r"(a[1]), "r"(a[2]), "r"(a[3]), "r"(b0), "r"(b1));
}
__device__ __forceinline__ void mma16816z(float (&d)[4], const uint32_t (&a)[4], uint32_t b0, uint32_t b1) {
    asm volatile(
        "mma.sync.aligned.m16n8k16.row.col.f32.bf16.bf16.f32 {%0,%1,%2,%3}, {%4,%5,%6,%7}, {%8,%9}, {%10,%10,%10,%10};"
        : "=f"(d[0]), "=f"(d[1]), "=f"(d[2]), "=f"(d[3])
        : "r"(a[0]), "r"(a[1]), "r"(a[2]), "r"(a[3]), "r"(b0), "r"(b1), "f"(0.0f));
}
__device__ __forceinline__ uint4 lds128(uint32_t addr) {
    uint4 v;
    asm volatile("ld.shared.v4.u32 {%0,%1,%2,%3}, [%4];" : "=r"(v.x), "=r"(v.y), "=r"(v.z), "=r"(v.w) : "r"(addr) : "memory");
    return v;
}
__device__ __forceinline__ uint2 lds64(uint32_t addr) {
    uint2 v;
    asm volatile("ld.shared.v2.u32 {%0,%1}, [%2];" : "=r"(v.x), "=r"(v.y) : "r"(addr) : "memory");
    return v;
}
__device__ __forceinline__ void sts32(uint32_t addr, uint32_t v) {
    asm volatile("st.shared.u32 [%0], %1;" ::"r"(addr), "r"(v) : "memory");
}
__device__ __forceinline__ void sts64(uint32_t addr, uint32_t a, uint32_t b) {
    asm volatile("st.shared.v2.u32 [%0], {%1,%2};" ::"r"(addr), "r"(a), "r"(b) : "memory");
}
__device__ __forceinline__ void sts16(uint32_t addr, uint16_t v) {
    asm volatile("st.shared.u16 [%0], %1;" ::"r"(addr), "h"(v) : "memory");
}
__device__ __forceinline__ void sts128(uint32_t addr, uint32_t a, uint32_t b, uint32_t c, uint32_t d) {
    asm volatile("st.shared.v4.u32 [%0], {%1,%2,%3,%4};" ::"r"(addr), "r"(a), "r"(b), "r"(c), "r"(d) : "memory");
}
__device__ __forceinline__ uint32_t lds32(uint32_t addr) {
    uint32_t v;
    asm volatile("ld.shared.u32 %0, [%1];" : "=r"(v) : "r"(addr) : "memory");
    return v;
}
__device__ __forceinline__ float ldsf(uint32_t addr) {
    float v;
    asm volatile("ld.shared.f32 %0, [%1];" : "=f"(v) : "r"(addr) : "memory");
    return v;
}

__device__ __forceinline__ uint32_t gtime32() {
    uint32_t t;
    asm volatile("mov.u32 %0, %%globaltimer_lo;" : "=r"(t) :: "memory");
    return t;
}

__device__ __forceinline__ void ln_stats(const float (&v0)[8], const float (&v1)[8], uint32_t red, int aw, int lane,
                                         uint32_t& m0, uint32_t& m1, float& d0, float& d1) {
    float a0 = ((v0[0] + v0[1]) + (v0[2] + v0[3])) + ((v0[4] + v0[5]) + (v0[6] + v0[7]));
    float a1 = ((v1[0] + v1[1]) + (v1[2] + v1[3])) + ((v1[4] + v1[5]) + (v1[6] + v1[7]));
    a0 *= 0.125f;
    a1 *= 0.125f;
    float q0 = 0.f, q1 = 0.f;
#pragma unroll
    for (int j = 0; j < 8; j++) {
        const float x = v0[j] - a0, y = v1[j] - a1;
        q0 += x * x;
        q1 += y * y;
    }
    float hn = 4.0f;
#pragma unroll
    for (int o = 1; o < 32; o <<= 1) {
        const float b0 = __shfl_xor_sync(0xffffffffu, a0, o), b1 = __shfl_xor_sync(0xffffffffu, a1, o);
        const float r0 = __shfl_xor_sync(0xffffffffu, q0, o), r1 = __shfl_xor_sync(0xffffffffu, q1, o);
        const float e0 = b0 - a0, e1 = b1 - a1;
        q0 = (q0 + r0) + e0 * e0 * hn;
        q1 = (q1 + r1) + e1 * e1 * hn;
        a0 = 0.5f * (a0 + b0);
        a1 = 0.5f * (a1 + b1);
        hn *= 2.0f;
    }
    if (lane == 0) sts128(red + aw * 16, __float_as_uint(a0), __float_as_uint(a1), __float_as_uint(q0), __float_as_uint(q1));
    __syncwarp();
    bar_sync(BAR_AUX, 128);
    const uint4 w0 = lds128(red), w1 = lds128(red + 16), w2 = lds128(red + 32), w3 = lds128(red + 48);
    const float mean0 = 0.25f * ((__uint_as_float(w0.x) + __uint_as_float(w1.x)) + (__uint_as_float(w2.x) + __uint_as_float(w3.x)));
    const float mean1 = 0.25f * ((__uint_as_float(w0.y) + __uint_as_float(w1.y)) + (__uint_as_float(w2.y) + __uint_as_float(w3.y)));
    float t0, t1, t2, t3;
    t0 = __uint_as_float(w0.x) - mean0; t1 = __uint_as_float(w1.x) - mean0;
    t2 = __uint_as_float(w2.x) - mean0; t3 = __uint_as_float(w3.x) - mean0;
    q0 = ((__uint_as_float(w0.z) + __uint_as_float(w1.z)) + (__uint_as_float(w2.z) + __uint_as_float(w3.z))) +
         256.0f * ((t0 * t0 + t1 * t1) + (t2 * t2 + t3 * t3));
    t0 = __uint_as_float(w0.y) - mean1; t1 = __uint_as_float(w1.y) - mean1;
    t2 = __uint_as_float(w2.y) - mean1; t3 = __uint_as_float(w3.y) - mean1;
    q1 = ((__uint_as_float(w0.w) + __uint_as_float(w1.w)) + (__uint_as_float(w2.w) + __uint_as_float(w3.w))) +
         256.0f * ((t0 * t0 + t1 * t1) + (t2 * t2 + t3 * t3));
    m0 = pack2(mean0, mean0);
    m1 = pack2(mean1, mean1);
    d0 = __fdividef(1.0f, bf16r(sqrt_fast(bf16r(bf16r(q0 * (1.0f / 1024.0f)) + 1e-5f))));
    d1 = __fdividef(1.0f, bf16r(sqrt_fast(bf16r(bf16r(q1 * (1.0f / 1024.0f)) + 1e-5f))));
}
__device__ __forceinline__ __nv_bfloat162 as_bf2(uint32_t w) { return *reinterpret_cast<__nv_bfloat162*>(&w); }
__device__ __forceinline__ uint32_t as_u32(__nv_bfloat162 v) { return *reinterpret_cast<uint32_t*>(&v); }
__device__ __forceinline__ uint32_t modulate2(uint32_t x, uint32_t m2, float rd, uint32_t c1, uint32_t s) {
    const uint32_t t = as_u32(__hsub2_rn(as_bf2(x), as_bf2(m2)));
    const uint32_t xn = pack2(bflo(t) * rd, bfhi(t) * rd);
    return as_u32(__hadd2_rn(__hmul2_rn(as_bf2(xn), as_bf2(c1)), as_bf2(s)));
}
__device__ __forceinline__ float sum4(uint32_t a, uint32_t b, uint32_t c, uint32_t d) {
    return (untag(a) + untag(b)) + (untag(c) + untag(d));
}

#define POLL_PASS(N, V, ADDR)                                                  \
    {                                                                          \
        _Pragma("unroll") for (int j = 0; j < N; j++) ldp4_if(V[j], ADDR, ~and4(V[j]) & tag); \
    }
#define POLL_DONE(N, V, A)                                                     \
    {                                                                          \
        A = tag;                                                               \
        _Pragma("unroll") for (int j = 0; j < N; j++) A &= and4(V[j]);         \
    }
#define POLL_INIT(N, V) { _Pragma("unroll") for (int j = 0; j < N; j++) V[j] = make_uint4(0, 0, 0, 0); }
#define POLL_LOOP(N, V, ADDR, SLEEP)                                           \
    {                                                                          \
        int n_ = 0;                                                            \
        uint32_t a_;                                                           \
        _Pragma("unroll 1") do {                                               \
            if (SLEEP && n_) __nanosleep(SLEEP);                               \
            POLL_PASS(N, V, ADDR);                                             \
            POLL_DONE(N, V, a_);                                               \
            spin_check(n_);                                                    \
        } while (!__all_sync(0xffffffffu, a_ != 0));                           \
    }
#define POLL(N, V, ADDR) { POLL_INIT(N, V); POLL_LOOP(N, V, ADDR, 0); }
#define POLLD(N, V, ADDR) { POLL_INIT(N, V); if (PS0) __nanosleep(PS0); POLL_LOOP(N, V, ADDR, PS1); }

__device__ __forceinline__ void box_coords(int c, int b, int& tmi, int& x0, int& y0) {
    const int hf = b & 1;
    if (b < 12) {
        tmi = 1; x0 = 128 * (c & 31) + 64 * hf; y0 = 256 * (c >> 5) + 64 * ((b - 4) >> 1);
    } else if (b < 28) {
        const int j = (b - 12) >> 1;
        tmi = 2 + (j >> 2); x0 = 64 * hf;
        y0 = (c >> 4) * SK + (SK - WIN) + 256 * (c & 15) + 64 * (j & 3);
    } else if (b < 34) {
        tmi = 0; x0 = 2048 + 192 * (c & 15) + 64 * ((b - 28) >> 1); y0 = 128 * (c >> 4) + 64 * hf;
    } else if (b < 42) {
        tmi = 4; x0 = 128 * (c & 7) + 64 * hf; y0 = 256 * (c >> 3) + 64 * ((b - 34) >> 1);
    } else if (b < 58) {
        if (c < 56) { tmi = 5; x0 = 64 * c; }
        else if (c < 112) { tmi = 6; x0 = 64 * (c - 56); }
        else { tmi = 0; x0 = 5120 + 64 * (c - 112); }
        y0 = 64 * (b - 42);
    } else {
        tmi = 7; x0 = (c < 56 ? 0 : 512) + 64 * (b - 58); y0 = 64 * (c < 56 ? c : c - 56);
    }
}

__global__ void __launch_bounds__(NTHREADS, 1) fused_kernel(const __grid_constant__ Params prm) {
    extern __shared__ __align__(1024) unsigned char smem_raw[];
    const uint32_t sm = smem_u32(smem_raw);
    const int c = blockIdx.x;
    const int warp = threadIdx.x >> 5, lane = threadIdx.x & 31;
    const uint32_t t0 = gtime32();
    uint64_t pol;
    asm volatile("createpolicy.fractional.L2::evict_first.b64 %0, 1.0;" : "=l"(pol));
    if (threadIdx.x == 0) {
        mbar_init(sm + SM_CXB, 1);
#pragma unroll
        for (int i = 0; i < 4; i++) mbar_init(sm + SM_FULL + i * 8, 1);
        asm volatile("fence.mbarrier_init.release.cluster;" ::: "memory");
        mbar_expect(sm + SM_CXB, 8192 + 16);
        bulk_g2s(sm + SM_CX, prm.c, 4096, sm + SM_CXB);
        bulk_g2s(sm + SM_CX + 4096, prm.x, 4096, sm + SM_CXB);
        bulk_g2s(sm + SM_EPOCH, prm.epoch + c * 8, 16, sm + SM_CXB);
#pragma unroll
        for (int b = 0; b < 4; b++) {
            mbar_expect(sm + SM_FULL + b * 8, BOX_BYTES);
            tma2d(sm + b * BOX_BYTES, &prm.tm[0], 64 * (c & 31), 256 * (c >> 5) + 64 * b, sm + SM_FULL + b * 8, pol);
        }
#pragma unroll
        for (int b = 4; b < 4 + NPF0; b++)
            tma2d_prefetch(&prm.tm[1], 128 * (c & 31) + 64 * (b & 1), 256 * (c >> 5) + 64 * ((b - 4) >> 1), pol);
    }
    if (warp >= 1 && warp <= 8)
        asm volatile("prefetch.global.L2 [%0];" ::"l"(prm.wmod + (size_t)(256 * (c >> 5) + threadIdx.x - 32) * 6144 + 64 * (c & 31)));
    const int nbox = c < 112 ? NBOX : 58;
    const int tau2 = c < 112 ? TAU2 : TAU3;

    if (warp == 12 || warp == 15) {
        const int par = warp & 1;
        if (lane == 0) {
            if (par == 0) {
#pragma unroll
                for (int i = 4; i < NPOS; i++) mbar_init(sm + SM_FULL + i * 8, 1);
            } else {
#pragma unroll
                for (int i = 0; i < NPOS; i++) mbar_init(sm + SM_EMPTY + i * 8, 4);
            }
            asm volatile("fence.mbarrier_init.release.cluster;" ::: "memory");
        }
        {
            int tmi, x0, y0;
            const int b = 4 + par + 2 * lane;
            box_coords(c, b, tmi, x0, y0);
            sts64(sm + SM_BOXT + b * 8, (uint32_t)x0 | ((uint32_t)tmi << 16), (uint32_t)y0);
        }
        __syncwarp();
        bar_arrive(BAR_INIT, NTHREADS);
        bar_sync(ACT_HH, 128);
        if (lane == 0) {
            int pos = 4 + par, ph = 0;
            uint2 e = lds64(sm + SM_BOXT + (4 + par) * 8);
            uint32_t due = t0 + (uint32_t)((2 + par) * TAU - LLEAD);
#pragma unroll 1
            for (int b = 4 + par; b < nbox; b += 2) {
                const int lag = (int)(gtime32() - due);
                due += b < 44 ? 2 * TAU : 2 * tau2;
                const int win = LW + min(max(lag, 0) >> LAGSH, LWX) + (b >= BEND ? LWE : 0);
                int wp = pos - win, wq = ph;
                if (wp < 0) { wp += NPOS; wq ^= 1; }
                const uint32_t fre = mbar_try(sm + SM_EMPTY + pos * 8, ph ^ 1);
                const uint32_t got = mbar_try(sm + SM_FULL + wp * 8, wq) | (b < win);
                const CUtensorMap* tl = &prm.tm[e.x >> 16];
                const int x0 = e.x & 0xFFFF, y0 = e.y;
                e = lds64(sm + SM_BOXT + b * 8 + 16);
                if (!fre) mbar_wait(sm + SM_EMPTY + pos * 8, ph ^ 1);
                const uint32_t fb = sm + SM_FULL + pos * 8;
                mbar_expect(fb, BOX_BYTES);
                if (!got) mbar_wait_soft(sm + SM_FULL + wp * 8, wq);
                tma2d(sm + pos * BOX_BYTES, tl, x0, y0, fb, pol);
                asm volatile("st.volatile.shared.u32 [%0], %1;" ::"r"(sm + SM_PROG + par * 4), "r"(b) : "memory");
                pos += 2;
                if (pos >= NPOS) { pos -= NPOS; ph ^= 1; }
            }
        }
        return;
    }

    if (warp == 14) {
        if (lane < 8) asm volatile("prefetch.tensormap [%0];" ::"l"(&prm.tm[lane]) : "memory");
#pragma unroll 1
        for (int b = 4 + lane; b < NBOX; b += 32) {
            int tmi, x0, y0;
            box_coords(c, b, tmi, x0, y0);
            sts64(sm + SM_BOXT2 + b * 8, (uint32_t)x0 | ((uint32_t)tmi << 16), (uint32_t)y0);
        }
        if (lane < 2) asm volatile("st.volatile.shared.u32 [%0], %1;" ::"r"(sm + SM_PROG + lane * 4), "r"(LW - 1) : "memory");
        __syncwarp();
        bar_arrive(ACT_HH, 128);
        bar_arrive(BAR_INIT, NTHREADS);
        if (lane == 0) {
            int b = 4 + NPF0, n = 0;
#pragma unroll 1
            while (b < nbox) {
                int L, L1;
                asm volatile("ld.volatile.shared.v2.u32 {%0,%1}, [%2];" : "=r"(L), "=r"(L1) : "r"(sm + SM_PROG) : "memory");
                L = max(L, L1);
                if (b <= L) b = L + 1;
                const int lag = (int)(gtime32() - t0) - ((b < 42 ? b * TAU : 42 * TAU + (b - 42) * tau2) - TLEAD);
                if (lag >= 0 && b <= L + (PD - LW) + min(lag >> LAGSH, PDX) && b < nbox) {
                    const uint2 e = lds64(sm + SM_BOXT2 + b * 8);
                    tma2d_prefetch(&prm.tm[e.x >> 16], e.x & 0xFFFF, e.y, pol);
                    b++;
                } else {
                    __nanosleep(20);
                    if (++n > SPIN_LIMIT) __trap();
                }
            }
        }
        return;
    }
    float* const scr = prm.scr;

    if (warp < 8) {
        const int grp = warp >> 2, cw = warp & 3;
        const int g = lane >> 2, t = lane & 3;
        const int mi = lane >> 3, r8 = lane & 7;
        const uint32_t red = sm + SM_RED;
        const uint32_t laneA = sm + (uint32_t)(((mi >> 1) * 8 + r8) * 128 + (((cw * 2 + (mi & 1)) ^ r8) << 4));
        const int lane_o = (g + (t >> 1) * 8) * 2 + (t & 1);
        const int lane_q = cw * 16 + g + (t >> 1) * 8 + (t & 1) * 4096;
        const int lane_v = OFF_P3 + c * 1024 + warp * 128 + (t * 8 + g) * 4;
        const uint32_t lane0 = lane == 0;
        const int lane_b = (t & 1) * 16 + g + (t >> 1) * 8;
        if (warp == 0) {
            __syncwarp();
            bar_arrive(BAR_AUX, 160);
            bar_arrive(ACT_HH, 128);
        }
        if (grp == 0) stp1(scr + lane_o + OFF_P1 + (c >> 5) * 4096 + (c & 31) * 128 + cw * 32, 0u);
        int pos = grp, ph = 0;
        float run[4] = {0.f, 0.f, 0.f, 0.f};
        uint32_t a[4][4][4];
#pragma unroll
        for (int j = 0; j < 3; j++)
#pragma unroll
            for (int i = 0; i < 4; i++) a[j][i][0] = a[j][i][1] = a[j][i][2] = a[j][i][3] = 0;
        bar_sync(BAR_INIT, NTHREADS);
        const uint32_t epoch = lds32(sm + SM_EPOCH), tag = 1u + (epoch & 1u);
        if (threadIdx.x < 8) prm.epoch[c * 8 + threadIdx.x] = epoch + 1;
        uint32_t dp = sm + SM_DESC + grp * 512;

#define LOAD_BOX(J, P, PH, RDY)                                                        \
    {                                                                                  \
        if (!(RDY)) mbar_wait(sm + SM_FULL + (P) * 8, PH);                             \
        const uint32_t pa = laneA + (P) * BOX_BYTES;                                   \
        _Pragma("unroll") for (int i = 0; i < 4; i++) ldsm4t(a[J][i], pa + i * 2048);  \
        mbar_arrive_if(sm + SM_EMPTY + (P) * 8, lane0);                                \
    }
#define MMA_BOX(J)                                                                     \
    {                                                                                  \
        mma16816z(e[J][0], a[J][0], bf[J][0].x, bf[J][0].y);                           \
        mma16816z(e[J][1], a[J][1], bf[J][0].z, bf[J][0].w);                           \
        mma16816(e[J][0], a[J][2], bf[J][1].x, bf[J][1].y);                            \
        mma16816(e[J][1], a[J][3], bf[J][1].z, bf[J][1].w);                            \
    }

#pragma unroll 1
        for (;;) {
            const uint4 d0 = lds128(dp), d1 = lds128(dp + 16);
            dp += 32;
            const uint32_t fl = d1.x;
            const bool pv = fl & U_PV;
            int p[4], q[4];
            p[0] = pos; q[0] = ph;
            {
                const int s1 = (fl & U_BOX0) ? 2 : 0, s2 = (fl & U_BOX1) ? 2 : 0, s3 = (fl & U_BOX2) ? 2 : 0;
                p[1] = p[0] + s1; q[1] = q[0]; if (p[1] >= NPOS) { p[1] -= NPOS; q[1] ^= 1; }
                p[2] = p[1] + s2; q[2] = q[1]; if (p[2] >= NPOS) { p[2] -= NPOS; q[2] ^= 1; }
                p[3] = p[2] + s3; q[3] = q[2]; if (p[3] >= NPOS) { p[3] -= NPOS; q[3] ^= 1; }
                pos = p[3] + 2;   ph = q[3];   if (pos >= NPOS) { pos -= NPOS; ph ^= 1; }
            }
            const uint32_t rdy = mbar_try(sm + SM_FULL + p[0] * 8, q[0]) & mbar_try(sm + SM_FULL + p[1] * 8, q[1]) &
                                 mbar_try(sm + SM_FULL + p[2] * 8, q[2]);
            if (fl & U_BOX0) LOAD_BOX(0, p[0], q[0], rdy);
            if (fl & U_BOX1) LOAD_BOX(1, p[1], q[1], rdy);
            if (fl & U_BOX2) LOAD_BOX(2, p[2], q[2], rdy);
            if (fl & U_LONG) LOAD_BOX(3, p[3], q[3], 0);
            const uint32_t ba = sm + d0.x + (pv ? g : (g & 1)) * 64 + t * 16;
            const uint32_t bblk = pv ? 512u : 128u, bstep = d0.y & 0xFFFF;
            uint32_t bst = d0.y >> 16;
            int outp = ((fl & U_QSTR) ? lane_q : lane_o + cw * d1.y) + d0.z;
            if (d1.z & 0xFF) bar_sync(d1.z & 0xFF, 384);
            uint4 bf[4][2];
            float e[4][2][4];
            if (fl & U_LONG) {
#pragma unroll
                for (int j = 0; j < 4; j++) {
                    const uint32_t bj = ba + bst + j * bstep;
                    bf[j][0] = lds128(bj);
                    bf[j][1] = lds128(bj + bblk);
                }
                bst += 4 * bstep;
                p[0] = pos; q[0] = ph;
#pragma unroll
                for (int j = 1; j < 4; j++) {
                    p[j] = p[j - 1] + 2; q[j] = q[j - 1];
                    if (p[j] >= NPOS) { p[j] -= NPOS; q[j] ^= 1; }
                }
                pos = p[3] + 2; ph = q[3];
                if (pos >= NPOS) { pos -= NPOS; ph ^= 1; }
                const uint32_t r2 = mbar_try(sm + SM_FULL + p[0] * 8, q[0]) & mbar_try(sm + SM_FULL + p[1] * 8, q[1]) &
                                    mbar_try(sm + SM_FULL + p[2] * 8, q[2]);
                MMA_BOX(0);
                MMA_BOX(1);
                MMA_BOX(2);
                MMA_BOX(3);
                LOAD_BOX(0, p[0], q[0], r2);
                LOAD_BOX(1, p[1], q[1], r2);
                LOAD_BOX(2, p[2], q[2], r2);
#pragma unroll
                for (int k = 0; k < 4; k++)
                    run[k] = ((e[0][0][k] + e[0][1][k]) + (e[1][0][k] + e[1][1][k])) +
                             ((e[2][0][k] + e[2][1][k]) + (e[3][0][k] + e[3][1][k]));
            }
            const uint32_t rdy3 = mbar_try(sm + SM_FULL + p[3] * 8, q[3]);
#pragma unroll
            for (int j = 0; j < 4; j++) {
                const uint32_t bj = ba + ((bst + j * bstep) & 4095);
                bf[j][0] = lds128(bj);
                bf[j][1] = lds128(bj + bblk);
            }
            MMA_BOX(0);
            MMA_BOX(1);
            MMA_BOX(2);
            if (rdy3) LOAD_BOX(3, p[3], q[3], 1);
#pragma unroll
            for (int j = 0; j < 3; j++) {
                const bool valid = fl & (U_BOX0 << j);
#pragma unroll
                for (int k = 0; k < 4; k++) run[k] += valid ? e[j][0][k] + e[j][1][k] : 0.f;
                if (j > 0) {
                    const uint32_t f = fl & U_FL1;
                    const float v = (t & 2) ? ((t & 1) ? run[3] : run[2]) : ((t & 1) ? run[1] : run[0]);
                    stp1_if(scr + outp, tagf(v, tag), f);
                    outp += f ? (int)d0.w : 0;
#pragma unroll
                    for (int k = 0; k < 4; k++) run[k] = f ? 0.f : run[k];
                }
            }
            if (!rdy3) LOAD_BOX(3, p[3], q[3], 0);
            MMA_BOX(3);
#pragma unroll
            for (int k = 0; k < 4; k++) run[k] += e[3][0][k] + e[3][1][k];
            {
                float v = (t & 2) ? ((t & 1) ? run[3] : run[2]) : ((t & 1) ? run[1] : run[0]);
                uint32_t st = (fl & (U_FL3 | U_PV | U_CMB)) == U_FL3;
                if (fl & (U_CMB | U_PV)) {
                    if (pv) {
                        stp4(scr + lane_v, tagf(run[0], tag), tagf(run[1], tag), tagf(run[2], tag), tagf(run[3], tag));
                    } else if (grp) {
                        sts32(sm + SM_CMB + (cw * 32 + lane) * 4, __float_as_uint(v));
                        bar_arrive(BAR_MMA, 256);
                    } else {
                        bar_sync(BAR_MMA, 256);
                        v += ldsf(sm + SM_CMB + (cw * 32 + lane) * 4);
                        st = 1;
                    }
                }
                stp1_if(scr + outp, tagf(v, tag), st);
            }
            if (!(fl & U_FL3)) continue;
            run[0] = run[1] = run[2] = run[3] = 0.f;
            bar_arrive_if((d1.z >> 8) & 0xFF, 384, d1.z & 0xFF00);
            bar_arrive_if(((d1.z >> 16) - 1) & 15, 288, d1.z >> 16);
            if (d1.w) {
                const uint4 z0 = lds128(dp + d1.w - 32), z1 = lds128(dp + d1.w - 16);
                float* const zo = scr + (((z1.x & U_QSTR) ? lane_q : ((z1.x & U_BSTR) ? lane_b : lane_o) + cw * z1.y) + z0.z);
                stp1_if(zo, 0u, !((z1.x & U_CMB) && grp));
                stp1_if(zo + 3 * (int)z0.w, 0u, z1.x & U_FL0);
                stp1_if(zo + (int)z0.w, 0u, z1.x & U_FL1);
                stp1_if(zo + 2 * (int)z0.w, 0u, z1.x & U_FL1);
            }
            if (!(fl & (U_QK | U_LAST | U_CLR))) continue;
            if (fl & U_LAST) break;
            if (fl & U_CLR) {
                stp4(scr + lane_v, 0u, 0u, 0u, 0u);
                if (warp == 7 && g == 0) stp4(scr + OFF_ML + c * 16 + t * 4, 0u, 0u, 0u, 0u);
                __syncwarp();
                continue;
            }
            {
                const uint32_t kA = sm + (uint32_t)((cw * 16 + (mi & 1) * 8 + r8) * 128);
#pragma unroll
                for (int j = 0; j < 2; j++) {
                    const int p0 = 12 + 2 * (grp + 2 * j);
#pragma unroll
                    for (int hf = 0; hf < 2; hf++) {
                        mbar_wait(sm + SM_FULL + (p0 + hf) * 8, 0);
#pragma unroll
                        for (int i = 0; i < 4; i++)
                            ldsm4(a[j * 2 + hf][i], kA + (p0 + hf) * BOX_BYTES + (((i * 2 + (mi >> 1)) ^ r8) << 4));
                        mbar_arrive_if(sm + SM_EMPTY + (p0 + hf) * 8, lane0);
                    }
                }
                pos = 20 + grp;
                bar_sync(ACT_Q, 384);
                uint4 qf[4];
#pragma unroll
                for (int p = 0; p < 4; p++) qf[p] = lds128(sm + SM_Q + p * 512 + g * 64 + t * 16);
                float sc[2][4];
#pragma unroll
                for (int j = 0; j < 2; j++) {
                    float e0[4], e1[4];
                    mma16816z(e0, a[j * 2][0], qf[0].x, qf[0].y);
                    mma16816z(e1, a[j * 2][1], qf[0].z, qf[0].w);
#pragma unroll
                    for (int p = 1; p < 4; p++) {
                        mma16816(e0, a[j * 2 + (p >> 1)][(2 * p) & 3], qf[p].x, qf[p].y);
                        mma16816(e1, a[j * 2 + (p >> 1)][(2 * p + 1) & 3], qf[p].z, qf[p].w);
                    }
                    const uint32_t r0 = pack2(e0[0] + e1[0], e0[1] + e1[1]), r1 = pack2(e0[2] + e1[2], e0[3] + e1[3]);
                    const uint32_t s0 = pack2(bflo(r0) * 0.08838834764831845f, bfhi(r0) * 0.08838834764831845f);
                    const uint32_t s1 = pack2(bflo(r1) * 0.08838834764831845f, bfhi(r1) * 0.08838834764831845f);
                    sc[j][0] = bflo(s0); sc[j][1] = bfhi(s0); sc[j][2] = bflo(s1); sc[j][3] = bfhi(s1);
                }
                float a0 = fmaxf(fmaxf(sc[0][0], sc[0][2]), fmaxf(sc[1][0], sc[1][2]));
                float a1 = fmaxf(fmaxf(sc[0][1], sc[0][3]), fmaxf(sc[1][1], sc[1][3]));
#pragma unroll
                for (int o = 4; o < 32; o <<= 1) {
                    a0 = fmaxf(a0, __shfl_xor_sync(0xffffffffu, a0, o));
                    a1 = fmaxf(a1, __shfl_xor_sync(0xffffffffu, a1, o));
                }
                sts64(red + 256 + t * 64 + warp * 8, __float_as_uint(a0), __float_as_uint(a1));
                bar_sync(BAR_MMA, 256);
#pragma unroll
                for (int w = 0; w < 4; w++) {
                    const uint4 u = lds128(red + 256 + t * 64 + w * 16);
                    a0 = fmaxf(a0, fmaxf(__uint_as_float(u.x), __uint_as_float(u.z)));
                    a1 = fmaxf(a1, fmaxf(__uint_as_float(u.y), __uint_as_float(u.w)));
                }
                float l0 = 0.f, l1 = 0.f;
#pragma unroll
                for (int j = 0; j < 2; j++) {
                    const uint32_t dst = sm + SM_P + (2 * (grp + 2 * j) + (cw >> 1)) * 512 + (g >> 1) * 16 + (cw & 1) * 8 +
                                         (g & 1) * 2 + t * 128;
                    const float p0 = exp_f(sc[j][0] - a0), p1 = exp_f(sc[j][1] - a1);
                    const float p2 = exp_f(sc[j][2] - a0), p3 = exp_f(sc[j][3] - a1);
                    l0 += p0 + p2;
                    l1 += p1 + p3;
                    const uint32_t u0 = pack2(p0, p1), u1 = pack2(p2, p3);
                    sts16(dst, (uint16_t)u0);
                    sts16(dst + 64, (uint16_t)(u0 >> 16));
                    sts16(dst + 4, (uint16_t)u1);
                    sts16(dst + 68, (uint16_t)(u1 >> 16));
                }
#pragma unroll
                for (int o = 4; o < 32; o <<= 1) {
                    l0 += __shfl_xor_sync(0xffffffffu, l0, o);
                    l1 += __shfl_xor_sync(0xffffffffu, l1, o);
                }
                sts64(red + 512 + t * 64 + warp * 8, __float_as_uint(l0), __float_as_uint(l1));
                bar_sync(BAR_MMA, 256);
                if (warp == 7) {
                    l0 = 0.f; l1 = 0.f;
#pragma unroll
                    for (int w = 0; w < 4; w++) {
                        const uint4 u = lds128(red + 512 + t * 64 + w * 16);
                        l0 += __uint_as_float(u.x) + __uint_as_float(u.z);
                        l1 += __uint_as_float(u.y) + __uint_as_float(u.w);
                    }
                    if (g == 0) stp4(scr + OFF_ML + c * 16 + t * 4, tagf(a0, tag), tagf(l0, tag), tagf(a1, tag), tagf(l1, tag));
                    __syncwarp();
                }
                bar_arrive(SIG_QK, 384);
            }
        }
        if (c < 112) {
            const uint4 d0 = lds128(dp);
            float* op = scr + (lane_b + cw * 1792 + d0.z);
            bar_sync(ACT_HH, 384);
            const uint4 b0 = lds128(sm + SM_HH + (g & 1) * 64 + t * 16), b1 = lds128(sm + SM_HH + 128 + (g & 1) * 64 + t * 16);
#pragma unroll 1
            for (int j = 0; j < 4; j++) {
                if (!mbar_try(sm + SM_FULL + pos * 8, ph)) mbar_wait(sm + SM_FULL + pos * 8, ph);
                const uint32_t pa = laneA + pos * BOX_BYTES;
                uint32_t wa[4][4];
#pragma unroll
                for (int i = 0; i < 4; i++) ldsm4t(wa[i], pa + i * 2048);
                float e0[4], e1[4], e2[4], e3[4];
                mma16816z(e0, wa[0], b0.x, b0.y);
                mma16816z(e1, wa[1], b0.z, b0.w);
                mma16816z(e2, wa[2], b1.x, b1.y);
                mma16816z(e3, wa[3], b1.z, b1.w);
                pos += 2;
                const float v0 = (t & 2) ? ((t & 1) ? e0[3] : e0[2]) : ((t & 1) ? e0[1] : e0[0]);
                const float v1 = (t & 2) ? ((t & 1) ? e1[3] : e1[2]) : ((t & 1) ? e1[1] : e1[0]);
                const float v2 = (t & 2) ? ((t & 1) ? e2[3] : e2[2]) : ((t & 1) ? e2[1] : e2[0]);
                const float v3 = (t & 2) ? ((t & 1) ? e3[3] : e3[2]) : ((t & 1) ? e3[1] : e3[0]);
                stp1(op, tagf((v0 + v2) + (v1 + v3), tag));
                op += 8 * 1792;
            }
        }
        return;
    }

    if (warp == 13) {
        {
            const int gp = lane >> 4, u = lane & 15;
            const uint32_t all = U_BOX0 | U_BOX1 | U_BOX2;
            uint32_t act = 0, bstep = 512, bst = 0, out = 0, ostep = 0, fl = all | U_FL3, bars = 0, rs = 32;
            const uint32_t clr = u == 0 ? 32 : (u <= 2 ? 2 * 32 : (u == 3 || (u == 4 && c < 112) ? 2 * 32 : 0));
            if (u == 0) {
                act = SM_SILU; bst = ((c >> 5) * 1024 + gp * 256 - 1024) & 4095;
                out = OFF_P1 + (c >> 5) * 4096 + (c & 31) * 128;
                fl = U_BOX2 | U_FL3 | U_CMB | U_CLR;
                bars = SIG_S1 << 8;
            } else if (u == 1) {
                act = SM_H; bstep = 256;
                out = OFF_P2 + (c >> 5) * 8192 + 128 * (c & 31) + 64 * gp;
                fl |= U_QSTR | U_QK;
                bars = ACT_H | (SIG_S2 << 8);
            } else if (u == 2) {
                act = SM_P; bstep = 1024;
                fl |= U_PV;
                bars = SIG_PV << 8;
            } else if (u == 3) {
                act = SM_SILU; bst = (c >> 4) * 512 + gp * 256; bstep = 0;
                rs = 512; ostep = 4 * 512;
                out = OFF_P1B + 12 * (c & 15) * 512 + ((c >> 4) * 2 + gp) * 32;
                fl = U_BOX1 | U_BOX2 | U_FL1 | U_FL2 | U_FL3;
                bars = (RS_S1B + 1) << 16;
            } else if (u == 4) {
                act = SM_O; bstep = 256;
                rs = 512;
                out = OFF_P4 + (8 * (c & 7) + 4 * gp) * 512 + (c >> 3) * 32;
                bars = ACT_O | (SIG_WO << 8) | ((RS_WO + 1) << 16);
            } else if (u == 5) {
                act = c < 112 ? SM_H2 : SM_SILU;
                out = OFF_GU + c * 128;
                bst = gp * 256;
                fl |= U_LONG | U_CMB | U_LAST;
                bars = (c < 112 ? ACT_H2 : 0) | (SIG_S5 << 8);
            } else {
                act = SM_HH; bstep = 0;
                rs = 1792; ostep = 8 * 1792;
                out = OFF_P6 + ((c < 56 ? 0 : 32) + 4 * gp) * 1792 + (c < 56 ? c : c - 56) * 32;
                fl |= U_FL0 | U_FL1 | U_FL2 | U_LAST | U_BSTR;
                bars = ACT_HH;
            }
            sts128(sm + SM_DESC + lane * 32, act, bstep | (bst << 16), out, ostep);
            sts128(sm + SM_DESC + lane * 32 + 16, fl, rs, bars, clr);
        }
        __syncwarp();
        bar_arrive(BAR_INIT, NTHREADS);
        const int r = c >> 1, pg = lane >> 3, q = lane & 7;
        const int col = 16 * r + 2 * q;
        float* const x1p = scr + OFF_X1 + pg * 2048 + col * 2;
        float* const csp = scr + OFF_CS + pg * 4096 + col * 2;
        float base[4];
        __nanosleep(2000);
        if (c & 1) {
            stp4(csp, 0u, 0u, 0u, 0u);
            stp4(csp + 2048, 0u, 0u, 0u, 0u);
        } else {
            stp4(x1p, 0u, 0u, 0u, 0u);
        }
        uint32_t tag;
        {
            const float* sa = scr + OFF_P1B + ((c & 1) * 64 + r) * 512 + lane * 4;
            const float* sb = scr + ((c & 1) ? OFF_P1B + 128 * 512 : OFF_P4) + r * 512 + lane * 4;
            bar_sync((c & 1) ? RS_S1B : RS_WO, 288);
            tag = 1u + (lds32(sm + SM_EPOCH) & 1u);
            {
                const uint32_t w0 = lds32(sm + SM_CX + 4096 + col * 2), w1 = lds32(sm + SM_CX + 6144 + col * 2);
                base[0] = bflo(w0); base[1] = bflo(w1); base[2] = bfhi(w0); base[3] = bfhi(w1);
            }
            uint4 v[8];
            POLL(8, v, (j < 4 ? sa + j * 128 : sb + (j - 4) * 128));
            float s[8];
#pragma unroll
            for (int h = 0; h < 2; h++) {
                s[4 * h + 0] = sum4(v[4 * h].x, v[4 * h + 1].x, v[4 * h + 2].x, v[4 * h + 3].x);
                s[4 * h + 1] = sum4(v[4 * h].y, v[4 * h + 1].y, v[4 * h + 2].y, v[4 * h + 3].y);
                s[4 * h + 2] = sum4(v[4 * h].z, v[4 * h + 1].z, v[4 * h + 2].z, v[4 * h + 3].z);
                s[4 * h + 3] = sum4(v[4 * h].w, v[4 * h + 1].w, v[4 * h + 2].w, v[4 * h + 3].w);
            }
#pragma unroll
            for (int e = 0; e < 8; e++) {
                s[e] += __shfl_xor_sync(0xffffffffu, s[e], 8);
                s[e] += __shfl_xor_sync(0xffffffffu, s[e], 16);
                s[e] = bf16r(s[e]);
            }
            if (c & 1) {
                stp4(csp, tagf(bf16r(1.0f + s[4]), tag), tagf(s[0], tag), tagf(bf16r(1.0f + s[5]), tag), tagf(s[1], tag));
                stp4(csp + 2048, tagf(bf16r(1.0f + s[6]), tag), tagf(s[2], tag), tagf(bf16r(1.0f + s[7]), tag), tagf(s[3], tag));
            } else {
#pragma unroll
                for (int e = 0; e < 4; e++) base[e] = bf16r(base[e] + bf16r(s[e] * s[4 + e]));
                stp4(x1p, tagf(base[0], tag), tagf(base[1], tag), tagf(base[2], tag), tagf(base[3], tag));
            }
        }
        if (!(c & 1)) {
            uint4 gv[1];
            POLL_INIT(1, gv);
            POLL_LOOP(1, gv, scr + OFF_GU + (7168 + col) * 2, 100);
            const float gb[4] = {bf16r(untag(gv[0].x)), bf16r(untag(gv[0].y)), bf16r(untag(gv[0].z)), bf16r(untag(gv[0].w))};
            if (pg < 2) {
                sts64(sm + SM_WS + pg * 128 + q * 8, __float_as_uint(pg ? base[1] : base[0]), __float_as_uint(pg ? base[3] : base[2]));
                sts64(sm + SM_WS + pg * 128 + 64 + q * 8, __float_as_uint(pg ? gb[1] : gb[0]), __float_as_uint(pg ? gb[3] : gb[2]));
            }
            __syncwarp();
            bar_arrive(RS_S5, 96);
        }
        return;
    }

    const int aw = warp - 8;
    const int ti = threadIdx.x - 256;
    const uint32_t red = sm + SM_RED;
    const int kp = 32 * (ti >> 4) + 8 * (ti & 3) + 2 * ((ti >> 2) & 3);
    const uint32_t pairoff = (ti >> 4) * 128 + (ti & 15) * 4;
    const int blk = ti >> 2, tt = ti & 3;
    const int k0 = 32 * blk + 2 * tt;

    uint32_t xk0, xk1, m0, m1;
    float d0, d1;
    {
        uint32_t cwd[2][4], xwd[2][4];
        bar_sync(BAR_AUX, 160);
        mbar_wait(sm + SM_CXB, 0);
#pragma unroll
        for (int b = 0; b < 2; b++)
#pragma unroll
            for (int j = 0; j < 4; j++) {
                cwd[b][j] = lds32(sm + SM_CX + (b * 1024 + k0 + 8 * j) * 2);
                xwd[b][j] = lds32(sm + SM_CX + 4096 + (b * 1024 + k0 + 8 * j) * 2);
            }
        xk0 = lds32(sm + SM_CX + 4096 + (256 * (c >> 5) + kp) * 2);
        xk1 = lds32(sm + SM_CX + 4096 + 2048 + (256 * (c >> 5) + kp) * 2);
#pragma unroll
        for (int b = 0; b < 2; b++) {
            uint32_t o[4];
#pragma unroll
            for (int j = 0; j < 4; j++) o[j] = pack2(silu_f(bflo(cwd[b][j])), silu_f(bfhi(cwd[b][j])));
            sts128(sm + SM_SILU + blk * 128 + b * 64 + tt * 16, o[0], o[1], o[2], o[3]);
        }
        bar_arrive(BAR_INIT, NTHREADS);
        float v0[8], v1[8];
#pragma unroll
        for (int j = 0; j < 4; j++) {
            v0[2 * j] = bflo(xwd[0][j]); v0[2 * j + 1] = bfhi(xwd[0][j]);
            v1[2 * j] = bflo(xwd[1][j]); v1[2 * j + 1] = bfhi(xwd[1][j]);
        }
        ln_stats(v0, v1, red, aw, lane, m0, m1, d0, d1);
    }
    const uint32_t tag = 1u + (lds32(sm + SM_EPOCH) & 1u);

    {
        const float* src = scr + OFF_P1 + (256 * (c >> 5) + kp) * 2;
        uint4 v[8];
        bar_sync(SIG_S1, 384);
        POLLD(8, v, src + (j & 3) * 4096 + (j >> 2) * 2048);
        const uint32_t one2 = 0x3f803f80u;
        const uint32_t sa0 = pack2(sum4(v[0].x, v[1].x, v[2].x, v[3].x), sum4(v[0].z, v[1].z, v[2].z, v[3].z));
        const uint32_t sa1 = pack2(sum4(v[0].y, v[1].y, v[2].y, v[3].y), sum4(v[0].w, v[1].w, v[2].w, v[3].w));
        const uint32_t ca0 = pack2(sum4(v[4].x, v[5].x, v[6].x, v[7].x), sum4(v[4].z, v[5].z, v[6].z, v[7].z));
        const uint32_t ca1 = pack2(sum4(v[4].y, v[5].y, v[6].y, v[7].y), sum4(v[4].w, v[5].w, v[6].w, v[7].w));
        sts32(sm + SM_H + pairoff, modulate2(xk0, m0, d0, as_u32(__hadd2_rn(as_bf2(one2), as_bf2(ca0))), sa0));
        sts32(sm + SM_H + pairoff + 64, modulate2(xk1, m1, d1, as_u32(__hadd2_rn(as_bf2(one2), as_bf2(ca1))), sa1));
        bar_arrive(ACT_H, 384);
    }
    {
        const float* src = scr + OFF_P2 + (c >> 4) * 1024 + ti * 8;
        uint4 v[8];
        bar_sync(SIG_S2, 384);
        POLLD(8, v, src + (j & 3) * 8192 + (j >> 2) * 4);
        const int head = ti >> 4, dq = ti & 15;
        const uint32_t dst = sm + SM_Q + (dq >> 2) * 512 + head * 64 + (dq & 3) * 4;
        sts32(dst, pack2(sum4(v[0].x, v[1].x, v[2].x, v[3].x), sum4(v[0].y, v[1].y, v[2].y, v[3].y)));
        sts32(dst + 16, pack2(sum4(v[0].z, v[1].z, v[2].z, v[3].z), sum4(v[0].w, v[1].w, v[2].w, v[3].w)));
        sts32(dst + 32, pack2(sum4(v[4].x, v[5].x, v[6].x, v[7].x), sum4(v[4].y, v[5].y, v[6].y, v[7].y)));
        sts32(dst + 48, pack2(sum4(v[4].z, v[5].z, v[6].z, v[7].z), sum4(v[4].w, v[5].w, v[6].w, v[7].w)));
        bar_arrive(ACT_Q, 384);
    }
    {
        const int b = ti >> 6, dt = (ti >> 3) & 7, g = ti & 7;
        const int hp = c >> 3, cta0 = (b * 4 + (hp >> 2)) * 16;
        {
            uint4 ml[1];
            bar_sync(SIG_QK, 384);
            POLLD(1, ml, scr + OFF_ML + (cta0 + (lane & 15)) * 16 + (hp & 3) * 4);
            const float ma = untag(ml[0].x), mb = untag(ml[0].z);
            float Ma = ma, Mb = mb;
#pragma unroll
            for (int o = 1; o < 16; o <<= 1) {
                Ma = fmaxf(Ma, __shfl_xor_sync(0xffffffffu, Ma, o));
                Mb = fmaxf(Mb, __shfl_xor_sync(0xffffffffu, Mb, o));
            }
            const float wa = exp_f(ma - Ma), wb = exp_f(mb - Mb);
            float La = wa * untag(ml[0].y), Lb = wb * untag(ml[0].w);
#pragma unroll
            for (int o = 1; o < 16; o <<= 1) {
                La += __shfl_xor_sync(0xffffffffu, La, o);
                Lb += __shfl_xor_sync(0xffffffffu, Lb, o);
            }
            sts64(sm + SM_WS + aw * 128 + (lane & 15) * 8, __float_as_uint(__fdividef(wa, La)),
                  __float_as_uint(__fdividef(wb, Lb)));
            __syncwarp();
        }
        const float* src = scr + OFF_P3 + cta0 * 1024 + dt * 128 + ((hp & 3) * 8 + g) * 4;
        uint4 v[16];
        bar_sync(SIG_PV, 384);
        POLLD(16, v, src + j * 1024);
        float o0 = 0.f, o1 = 0.f, o2 = 0.f, o3 = 0.f;
#pragma unroll
        for (int s = 0; s < 16; s += 2) {
            const uint4 w = lds128(sm + SM_WS + aw * 128 + s * 8);
            o0 += __uint_as_float(w.x) * untag(v[s].x) + __uint_as_float(w.z) * untag(v[s + 1].x);
            o1 += __uint_as_float(w.y) * untag(v[s].y) + __uint_as_float(w.w) * untag(v[s + 1].y);
            o2 += __uint_as_float(w.x) * untag(v[s].z) + __uint_as_float(w.z) * untag(v[s + 1].z);
            o3 += __uint_as_float(w.y) * untag(v[s].w) + __uint_as_float(w.w) * untag(v[s + 1].w);
        }
        const uint32_t dst = sm + SM_O + (dt >> 1) * 128 + b * 64 + (g >> 1) * 16 + (dt & 1) * 8 + (g & 1) * 2;
        const uint32_t u0 = pack2(o0, o1), u1 = pack2(o2, o3);
        sts16(dst, (uint16_t)u0);
        sts16(dst + 512, (uint16_t)(u0 >> 16));
        sts16(dst + 4, (uint16_t)u1);
        sts16(dst + 516, (uint16_t)(u1 >> 16));
        bar_arrive(ACT_O, 384);
    }
    if (c < 112) {
        uint4 cs[4];
        bar_sync(SIG_WO, 384);
        {
            const float* src = scr + OFF_CS + (c & 3) * 4096 + k0 * 2;
            uint4 w8[8];
            POLL(8, w8, src + 16 * (j >> 1) + 2048 * (j & 1));
#pragma unroll
            for (int j = 0; j < 4; j++)
                cs[j] = make_uint4(__byte_perm(w8[2 * j].x, w8[2 * j + 1].x, 0x7632), __byte_perm(w8[2 * j].y, w8[2 * j + 1].y, 0x7632),
                                   __byte_perm(w8[2 * j].z, w8[2 * j + 1].z, 0x7632), __byte_perm(w8[2 * j].w, w8[2 * j + 1].w, 0x7632));
        }
        const float* xsrc = scr + OFF_X1 + (c & 3) * 2048 + k0 * 2;
        uint4 xv[4];
        POLL_INIT(4, xv);
        if (XS0) __nanosleep(XS0);
        POLL_LOOP(4, xv, xsrc + 16 * j, XS1);
        float v0[8], v1[8];
#pragma unroll
        for (int j = 0; j < 4; j++) {
            v0[2 * j] = untag(xv[j].x); v1[2 * j] = untag(xv[j].y);
            v0[2 * j + 1] = untag(xv[j].z); v1[2 * j + 1] = untag(xv[j].w);
        }
        uint32_t n0, n1;
        float e0, e1;
        ln_stats(v0, v1, red + 64, aw, lane, n0, n1, e0, e1);
        uint32_t o0[4], o1[4];
#pragma unroll
        for (int j = 0; j < 4; j++) {
            o0[j] = modulate2(__byte_perm(xv[j].x, xv[j].z, 0x7632), n0, e0, cs[j].x, cs[j].y);
            o1[j] = modulate2(__byte_perm(xv[j].y, xv[j].w, 0x7632), n1, e1, cs[j].z, cs[j].w);
        }
        sts128(sm + SM_H2 + blk * 128 + tt * 16, o0[0], o0[1], o0[2], o0[3]);
        sts128(sm + SM_H2 + blk * 128 + 64 + tt * 16, o1[0], o1[1], o1[2], o1[3]);
        bar_arrive(ACT_H2, 384);
    }
    bar_sync(SIG_S5, 384);
    if (c < 112) {
        if (aw == 0) {
            const float* gsrc = scr + OFF_GU + (64 * (c < 56 ? c : c - 56) + kp) * 2;
            uint4 gv[2];
            POLL(2, gv, gsrc + j * 7168);
            const uint4 gt = gv[0], up = gv[1];
            const uint32_t g0 = pack2(untag(gt.x), untag(gt.z)), g1 = pack2(untag(gt.y), untag(gt.w));
            const uint32_t u0 = pack2(untag(up.x), untag(up.z)), u1 = pack2(untag(up.y), untag(up.w));
            const uint32_t s0 = pack2(silu_f(bflo(g0)), silu_f(bfhi(g0))), s1 = pack2(silu_f(bflo(g1)), silu_f(bfhi(g1)));
            sts32(sm + SM_HH + pairoff, as_u32(__hmul2_rn(as_bf2(s0), as_bf2(u0))));
            sts32(sm + SM_HH + pairoff + 64, as_u32(__hmul2_rn(as_bf2(s1), as_bf2(u1))));
        }
        bar_arrive(ACT_HH, 384);
    }
    if (!(c & 1) && (aw == 1 || aw == 2)) {
        const int b = aw - 1, q4 = lane & 3;
        const float* sp = scr + OFF_P6 + (c >> 1) * 1792 + (lane >> 2) * 32 + b * 16 + q4 * 4;
        uint4 v[7];
        POLL_INIT(7, v);
        bar_sync(RS_S5, 96);
        const uint4 xb = lds128(sm + SM_WS + b * 128 + q4 * 16), gq = lds128(sm + SM_WS + b * 128 + 64 + q4 * 16);
        POLL_LOOP(7, v, sp + j * 256, 0);
        float s[4];
        s[0] = sum4(v[0].x, v[1].x, v[2].x, v[3].x) + ((untag(v[4].x) + untag(v[5].x)) + untag(v[6].x));
        s[1] = sum4(v[0].y, v[1].y, v[2].y, v[3].y) + ((untag(v[4].y) + untag(v[5].y)) + untag(v[6].y));
        s[2] = sum4(v[0].z, v[1].z, v[2].z, v[3].z) + ((untag(v[4].z) + untag(v[5].z)) + untag(v[6].z));
        s[3] = sum4(v[0].w, v[1].w, v[2].w, v[3].w) + ((untag(v[4].w) + untag(v[5].w)) + untag(v[6].w));
#pragma unroll
        for (int o = 4; o < 32; o <<= 1)
#pragma unroll
            for (int e = 0; e < 4; e++) s[e] += __shfl_xor_sync(0xffffffffu, s[e], o);
        const uint32_t f0 = pack2(s[0], s[1]), f1 = pack2(s[2], s[3]);
        const uint32_t g0 = __byte_perm(gq.x, gq.y, 0x7632), g1 = __byte_perm(gq.z, gq.w, 0x7632);
        const uint32_t x0 = __byte_perm(xb.x, xb.y, 0x7632), x1 = __byte_perm(xb.z, xb.w, 0x7632);
        uint2 w;
        w.x = as_u32(__hadd2_rn(as_bf2(x0), __hmul2_rn(as_bf2(g0), as_bf2(f0))));
        w.y = as_u32(__hadd2_rn(as_bf2(x1), __hmul2_rn(as_bf2(g1), as_bf2(f1))));
        if (lane < 4) *reinterpret_cast<uint2*>(prm.out + b * 1024 + 8 * c + q4 * 4) = w;
    }
}

typedef CUresult (*EncodeFn)(CUtensorMap*, CUtensorMapDataType, cuuint32_t, void*, const cuuint64_t*, const cuuint64_t*,
                             const cuuint32_t*, const cuuint32_t*, CUtensorMapInterleave, CUtensorMapSwizzle,
                             CUtensorMapL2promotion, CUtensorMapFloatOOBfill);

void make_map(EncodeFn enc, CUtensorMap* tm, const void* base, uint64_t cols, uint64_t rows) {
    cuuint64_t gd[2] = {cols, rows};
    cuuint64_t gs[1] = {cols * 2};
    cuuint32_t bd[2] = {64, 64};
    cuuint32_t es[2] = {1, 1};
    enc(tm, CU_TENSOR_MAP_DATA_TYPE_BFLOAT16, 2, const_cast<void*>(base), gd, gs, bd, es, CU_TENSOR_MAP_INTERLEAVE_NONE,
        CU_TENSOR_MAP_SWIZZLE_128B, CU_TENSOR_MAP_L2_PROMOTION_L2_128B, CU_TENSOR_MAP_FLOAT_OOB_FILL_NONE);
}

}

extern "C" void kernel_launch(void* const* d_in, const int* in_sizes, int n_in, void* d_out, int out_size) {
    static EncodeFn enc = nullptr;
    static float* scr_ptr = nullptr;
    static unsigned* epoch_ptr = nullptr;
    if (!enc) {
        cudaGetSymbolAddress((void**)&scr_ptr, g_scr);
        cudaGetSymbolAddress((void**)&epoch_ptr, g_epoch);
        cudaDriverEntryPointQueryResult qr;
        cudaGetDriverEntryPoint("cuTensorMapEncodeTiled", (void**)&enc, cudaEnableDefault, &qr);
        cudaFuncSetAttribute(fused_kernel, cudaFuncAttributeMaxDynamicSharedMemorySize, SM_TOTAL);
    }
    Params p;
    make_map(enc, &p.tm[0], d_in[10], 6144, 1024);
    make_map(enc, &p.tm[1], d_in[3], 4096, 1024);
    make_map(enc, &p.tm[2], d_in[1], 128, (uint64_t)8 * SK);
    make_map(enc, &p.tm[3], d_in[2], 128, (uint64_t)8 * SK);
    make_map(enc, &p.tm[4], d_in[4], 1024, 4096);
    make_map(enc, &p.tm[5], d_in[6], 3584, 1024);
    make_map(enc, &p.tm[6], d_in[7], 3584, 1024);
    make_map(enc, &p.tm[7], d_in[8], 1024, 3584);
    p.x = (const __nv_bfloat16*)d_in[0];
    p.c = (const __nv_bfloat16*)d_in[9];
    p.out = (__nv_bfloat16*)d_out;
    p.scr = scr_ptr;
    p.wmod = (const __nv_bfloat16*)d_in[10];
    p.epoch = epoch_ptr;
    fused_kernel<<<NCTA, NTHREADS, SM_TOTAL>>>(p);
}
```
